```python
import torch

def _softmax(x, axis=-1):
    return torch.softmax(x, dim=axis)
def _gelu(x):
    return torch.nn.functional.gelu(x, approximate="tanh")
def _silu(x):
    return torch.nn.functional.silu(x)
def _sigmoid(x):
    return torch.sigmoid(x)
def _layernorm(x, axis=-1, eps=1e-5):
    m = x.mean(dim=axis, keepdim=True)
    v = x.var(dim=axis, keepdim=True, unbiased=False)
    return (x - m) / torch.sqrt(v + eps)
def _scatter_add(tgt, idx, src, axis=0):
    return tgt.clone().index_add_(axis, idx, src)
def _segment_sum(src, seg, n):
    out = torch.zeros((n,) + src.shape[1:], dtype=src.dtype)
    return out.index_add_(0, seg, src)
def _pad(x, pw):
    flat = tuple(v for pair in reversed(pw) for v in pair)
    return torch.nn.functional.pad(x, flat)

kernel_name = 'gather_scatter__hybrid_graph_tf_exphormer__graph'

def setup_inputs():

    _w = (lambda a: (lambda t: t.to(torch.bfloat16) if t.is_floating_point() else t)(torch.as_tensor(a)))
    N, deg, D = 50000, 16, 64
    E = N * deg
    exp_deg = 4
    Ee = N * exp_deg
    src = (lambda lo, hi, *s: torch.randint(lo, hi, s))(0, N, E).to(torch.int64)
    dst = (lambda lo, hi, *s: torch.randint(lo, hi, s))(0, N, E).to(torch.int64)
    esrc = (lambda lo, hi, *s: torch.randint(lo, hi, s))(0, N, Ee).to(torch.int64)
    edst = torch.repeat_interleave(torch.arange(N), exp_deg).to(torch.int64)
    deg_cnt = torch.bincount(dst, minlength=N).to(float) + 1.0
    return {
        "x": _w((lambda *s: torch.randn(*s, dtype=torch.bfloat16) * 0.05)(N, D)),
        "src": _w(src),
        "dst": _w(dst),
        "esrc": _w(esrc),
        "edst": _w(edst),
        "deg_inv_sqrt": _w(1.0 / (lambda _x: torch.sqrt(torch.as_tensor(_x)))(deg_cnt)),
        "w_l": _w((lambda *s: torch.randn(*s, dtype=torch.bfloat16) * 0.05)(D, D)),
        "wq": _w((lambda *s: torch.randn(*s, dtype=torch.bfloat16) * 0.05)(D, D)),
        "wk": _w((lambda *s: torch.randn(*s, dtype=torch.bfloat16) * 0.05)(D, D)),
        "wv": _w((lambda *s: torch.randn(*s, dtype=torch.bfloat16) * 0.05)(D, D)),
    }

def reference(x, src, dst, esrc, edst, deg_inv_sqrt, w_l, wq, wk, wv):
    N, D = x.shape
    h = x @ w_l
    msg = h[src] * deg_inv_sqrt[src, None] * deg_inv_sqrt[dst, None]
    h_local = _segment_sum(msg, dst, N)
    q = x @ wq
    k = x @ wk
    v = x @ wv
    e = (q[edst] * k[esrc]).sum(-1) * (D ** -0.5)
    exp_e = torch.exp(e)
    denom = _segment_sum(exp_e[:, None], edst, N)[:, 0] + 1e-9
    alpha = exp_e / denom[edst]
    h_attn = _segment_sum(alpha[:, None] * v[esrc], edst, N)
    return h_local + h_attn
```

```cpp
#include <cuda_runtime.h>
#include <cuda_bf16.h>
#include <stdint.h>

namespace {

constexpr int N_NODES  = 50000;
constexpr int N_EDGES  = 800000;
constexpr int N_XEDGES = 200000;
constexpr int N_TILES  = N_NODES / 16;
constexpr int NW       = 24;
constexpr int NT       = NW * 32;
constexpr int NPC      = NW * 16;
constexpr int NCTA     = (N_NODES + NPC - 1) / NPC;
constexpr int NPROD    = NT / 6;
constexpr int EC       = NT * 8;
constexpr int EX       = N_EDGES / NPROD - EC;
constexpr int NCHK     = (N_NODES + NPROD - 1) / NPROD;
constexpr int MBS      = 352;
constexpr int GBLK     = NPROD * 96;
constexpr int GBKT     = 4 * GBLK;
#define KR 17
constexpr int NRANGE   = KR;
constexpr int NKEY     = NRANGE * NW;
constexpr int CAPR     = 352;
constexpr int STG      = NW * 2048;

static_assert(NPROD * (EC + EX) == N_EDGES && EX <= NT && NCHK <= NT, "edge slices");
static_assert(NPROD <= NCTA && NT % 6 == 0 && NKEY + 32 <= 512, "mapping");

constexpr int SM_W     = 0;
constexpr int SM_STAGE = 3 * 8192;
constexpr int SM_MB    = SM_STAGE;
constexpr int SM_TABLE = SM_STAGE + STG;
constexpr int TAB0     = (N_NODES * 2 - 2 * 8192 - NCHK * 16) / 128 * 128;
constexpr int SM_WQK   = SM_TABLE + TAB0;
constexpr int SM_WR    = SM_TABLE + N_NODES * 2;
constexpr int SM_S16   = SM_WR + NW * CAPR * 4;
constexpr int SM_AL    = SM_S16 + NW * CAPR * 2;
constexpr int SM_DIS   = SM_AL + NW * 128;
constexpr int SM_HIST  = SM_DIS + NPC * 2;
constexpr int SM_CNT   = SM_HIST + 136 * 4;
constexpr int SM_MISC  = SM_CNT + (NKEY + 32) * 4;
constexpr int SM_TOTAL = SM_MISC + 16;
constexpr int NFILL    = NW * CAPR * 6 / 16;
static_assert(NCTA * MBS <= STG && 2 * STG <= N_NODES * 2 && SM_WR % 16 == 0 && SM_MISC % 8 == 0, "layout");
static_assert(SM_TOTAL <= 232448 && SM_TABLE + 0x20000 <= SM_TOTAL, "shared memory");
static_assert((SM_MISC - SM_HIST) / 4 <= NT && 4 * NT * 16 + EX * 8 <= NFILL * 16, "staging");

__device__ __align__(128) unsigned char g_rec[NCTA * GBKT];
__device__ uint32_t g_epoch[NCTA];

#define PROF(i) do {} while (0)

__device__ __forceinline__ void mma16816(float (&d)[4], uint32_t a0, uint32_t a1, uint32_t a2, uint32_t a3,
                                         uint32_t b0, uint32_t b1) {
    asm volatile("mma.sync.aligned.m16n8k16.row.col.f32.bf16.bf16.f32 {%0,%1,%2,%3}, {%4,%5,%6,%7}, {%8,%9}, {%0,%1,%2,%3};"
                 : "+f"(d[0]), "+f"(d[1]), "+f"(d[2]), "+f"(d[3])
                 : "r"(a0), "r"(a1), "r"(a2), "r"(a3), "r"(b0), "r"(b1));
}
__device__ __forceinline__ void mma16816_z(float (&d)[4], uint32_t a0, uint32_t a1, uint32_t a2, uint32_t a3,
                                           uint32_t b0, uint32_t b1) {
    asm volatile("mma.sync.aligned.m16n8k16.row.col.f32.bf16.bf16.f32 {%0,%1,%2,%3}, {%4,%5,%6,%7}, {%8,%9}, {%10,%10,%10,%10};"
                 : "=f"(d[0]), "=f"(d[1]), "=f"(d[2]), "=f"(d[3])
                 : "r"(a0), "r"(a1), "r"(a2), "r"(a3), "r"(b0), "r"(b1), "f"(0.f));
}
__device__ __forceinline__ void ldsm4(uint32_t& r0, uint32_t& r1, uint32_t& r2, uint32_t& r3, uint32_t addr) {
    asm volatile("ldmatrix.sync.aligned.m8n8.x4.shared.b16 {%0,%1,%2,%3}, [%4];"
                 : "=r"(r0), "=r"(r1), "=r"(r2), "=r"(r3) : "r"(addr) : "memory");
}
__device__ __forceinline__ void ldsm4t(uint32_t (&r)[4], uint32_t addr) {
    asm volatile("ldmatrix.sync.aligned.m8n8.x4.trans.shared.b16 {%0,%1,%2,%3}, [%4];"
                 : "=r"(r[0]), "=r"(r[1]), "=r"(r[2]), "=r"(r[3]) : "r"(addr) : "memory");
}
__device__ __forceinline__ void stsm4(uint32_t addr, uint32_t r0, uint32_t r1, uint32_t r2, uint32_t r3) {
    asm volatile("stmatrix.sync.aligned.m8n8.x4.shared.b16 [%0], {%1,%2,%3,%4};"
                 :: "r"(addr), "r"(r0), "r"(r1), "r"(r2), "r"(r3) : "memory");
}
__device__ __forceinline__ uint32_t pack_bf16(float lo, float hi) {
    uint32_t r;
    asm("cvt.rn.bf16x2.f32 %0, %1, %2;" : "=r"(r) : "f"(hi), "f"(lo));
    return r;
}
__device__ __forceinline__ uint32_t fma_bf2(uint32_t a, uint32_t b, uint32_t c) {
    uint32_t r;
    asm volatile("fma.rn.bf16x2 %0, %1, %2, %3;" : "=r"(r) : "r"(a), "r"(b), "r"(c));
    return r;
}
__device__ __forceinline__ uint32_t mul_bf2(uint32_t a, uint32_t b) {
    uint32_t r;
    asm volatile("mul.rn.bf16x2 %0, %1, %2;" : "=r"(r) : "r"(a), "r"(b));
    return r;
}
__device__ __forceinline__ uint32_t add_bf2(uint32_t a, uint32_t b) {
    uint32_t r;
    asm("add.rn.bf16x2 %0, %1, %2;" : "=r"(r) : "r"(a), "r"(b));
    return r;
}
__device__ __forceinline__ uint32_t prmt(uint32_t a, uint32_t b, uint32_t s) {
    uint32_t r;
    asm("prmt.b32 %0, %1, %2, %3;" : "=r"(r) : "r"(a), "r"(b), "r"(s));
    return r;
}
__device__ __forceinline__ uint32_t eq_lo2(uint32_t a, uint32_t b) {
    uint32_t r;
    asm("{ .reg .b16 l, h; .reg .b32 c; mov.b32 {l, h}, %2; mov.b32 c, {l, l}; set.eq.u32.f16x2 %0, %1, c; }" : "=r"(r) : "r"(a), "r"(b));
    return r;
}
__device__ __forceinline__ uint32_t eq_hi2(uint32_t a, uint32_t b) {
    uint32_t r;
    asm("{ .reg .b16 l, h; .reg .b32 c; mov.b32 {l, h}, %2; mov.b32 c, {h, h}; set.eq.u32.f16x2 %0, %1, c; }" : "=r"(r) : "r"(a), "r"(b));
    return r;
}
__device__ __forceinline__ float ex2(float x) {
    float r;
    asm("ex2.approx.ftz.f32 %0, %1;" : "=f"(r) : "f"(x));
    return r;
}
__device__ __forceinline__ void cp16(uint32_t dst, const void* src) {
    asm volatile("cp.async.cg.shared.global [%0], [%1], 16;" :: "r"(dst), "l"(src) : "memory");
}
__device__ __forceinline__ void cp4(uint32_t dst, const void* src) {
    asm volatile("cp.async.ca.shared.global [%0], [%1], 4;" :: "r"(dst), "l"(src) : "memory");
}
__device__ __forceinline__ void cp16_row(uint32_t dst, const char* xl, uint32_t s) {
    asm volatile("{ .reg .pred p; .reg .b64 a; setp.ne.u32 p, %2, 0xFFFF; mad.wide.u32 a, %2, 128, %1; @p cp.async.cg.shared.global [%0], [a], 16; }"
                 :: "r"(dst), "l"(xl), "r"(s) : "memory");
}
__device__ __forceinline__ void cp_commit() { asm volatile("cp.async.commit_group;" ::: "memory"); }
template <int N> __device__ __forceinline__ void cp_wait() { asm volatile("cp.async.wait_group %0;" :: "n"(N) : "memory"); }
__device__ __forceinline__ void fence_async() { asm volatile("fence.proxy.async.shared::cta;" ::: "memory"); }
__device__ __forceinline__ void wsync() { asm volatile("bar.warp.sync 0xffffffff;" ::: "memory"); }
__device__ __forceinline__ uint4 ldg_stream(const void* p) {
    uint4 v;
    asm volatile("ld.global.L1::no_allocate.v4.u32 {%0,%1,%2,%3}, [%4];" : "=r"(v.x), "=r"(v.y), "=r"(v.z), "=r"(v.w) : "l"(p) : "memory");
    return v;
}
__device__ __forceinline__ uint2 ldg64(const void* p) {
    uint2 v;
    asm volatile("ld.global.L1::no_allocate.v2.u32 {%0,%1}, [%2];" : "=r"(v.x), "=r"(v.y) : "l"(p) : "memory");
    return v;
}
__device__ __forceinline__ uint4 lds128(uint32_t a) {
    uint4 v;
    asm volatile("ld.shared.v4.u32 {%0,%1,%2,%3}, [%4];" : "=r"(v.x), "=r"(v.y), "=r"(v.z), "=r"(v.w) : "r"(a) : "memory");
    return v;
}
__device__ __forceinline__ uint2 lds64(uint32_t a) {
    uint2 v;
    asm volatile("ld.shared.v2.u32 {%0,%1}, [%2];" : "=r"(v.x), "=r"(v.y) : "r"(a) : "memory");
    return v;
}
__device__ __forceinline__ uint32_t lds32(uint32_t a) {
    uint32_t v;
    asm volatile("ld.shared.u32 %0, [%1];" : "=r"(v) : "r"(a) : "memory");
    return v;
}
__device__ __forceinline__ uint32_t lds16(uint32_t a) {
    uint32_t v;
    asm volatile("ld.shared.u16 %0, [%1];" : "=r"(v) : "r"(a) : "memory");
    return v;
}
__device__ __forceinline__ void sts16(uint32_t a, uint32_t v) { asm volatile("st.shared.u16 [%0], %1;" :: "r"(a), "r"(v) : "memory"); }
__device__ __forceinline__ void sts32(uint32_t a, uint32_t v) { asm volatile("st.shared.u32 [%0], %1;" :: "r"(a), "r"(v) : "memory"); }
__device__ __forceinline__ void sts64(uint32_t a, uint32_t x, uint32_t y) {
    asm volatile("st.shared.v2.u32 [%0], {%1,%2};" :: "r"(a), "r"(x), "r"(y) : "memory");
}
__device__ __forceinline__ void sts128(uint32_t a, uint32_t v) {
    asm volatile("st.shared.v4.u32 [%0], {%1,%1,%1,%1};" :: "r"(a), "r"(v) : "memory");
}
__device__ __forceinline__ uint32_t atoms_add(uint32_t a, uint32_t v) {
    uint32_t r;
    asm volatile("atom.shared.add.u32 %0, [%1], %2;" : "=r"(r) : "r"(a), "r"(v) : "memory");
    return r;
}
__device__ __forceinline__ void sts128v(uint32_t a, uint32_t x, uint32_t y, uint32_t z, uint32_t w) {
    asm volatile("st.shared.v4.u32 [%0], {%1,%2,%3,%4};" :: "r"(a), "r"(x), "r"(y), "r"(z), "r"(w) : "memory");
}
__device__ __forceinline__ uint4 ldg128(const void* p) {
    uint4 v;
    asm volatile("ld.global.v4.u32 {%0,%1,%2,%3}, [%4];" : "=r"(v.x), "=r"(v.y), "=r"(v.z), "=r"(v.w) : "l"(p) : "memory");
    return v;
}
__device__ __forceinline__ uint32_t ldg32(const void* p) {
    uint32_t v;
    asm volatile("ld.global.L1::no_allocate.u32 %0, [%1];" : "=r"(v) : "l"(p) : "memory");
    return v;
}
__device__ __forceinline__ uint32_t rec_key(uint32_t r) { return (r >> 18) & 0x7FCu; }
__device__ __forceinline__ uint32_t rec_count(uint32_t sb, uint32_t r) {
    asm volatile("red.shared.add.u32 [%0], 1;" :: "r"(sb + SM_CNT + rec_key(r)) : "memory");
    return (r & 0xF0000u) | lds16(sb + SM_TABLE + (r & 0xFFFFu) * 2);
}
__device__ __forceinline__ void count4(uint4& w, const uint4& r, uint32_t sb) {
    w.x = rec_count(sb, r.x); w.y = rec_count(sb, r.y); w.z = rec_count(sb, r.z); w.w = rec_count(sb, r.w);
}
__device__ __forceinline__ void rec_put(uint32_t a, uint32_t sofs, uint32_t r, uint32_t w) {
    asm volatile("{ .reg .pred p; .reg .b32 s; setp.lt.u32 p, %4, %5; shr.u32 s, %0, 1; add.u32 s, s, %1;"
                 " @p st.shared.u32 [%0], %3; @p st.shared.u16 [s], %2; }"
                 :: "r"(a), "r"(sofs), "r"(r), "r"(w), "r"(rec_key(r)), "n"(NKEY * 4) : "memory");
}
__device__ __forceinline__ void place4(const uint4& r, const uint4& w, uint32_t sb) {
    const uint32_t sofs = sb + SM_S16 - (sb + SM_WR) / 2;
    const uint32_t a0 = atoms_add(sb + SM_CNT + rec_key(r.x), 4u), a1 = atoms_add(sb + SM_CNT + rec_key(r.y), 4u);
    const uint32_t a2 = atoms_add(sb + SM_CNT + rec_key(r.z), 4u), a3 = atoms_add(sb + SM_CNT + rec_key(r.w), 4u);
    rec_put(a0, sofs, r.x, w.x); rec_put(a1, sofs, r.y, w.y); rec_put(a2, sofs, r.z, w.z); rec_put(a3, sofs, r.w, w.w);
}
__device__ __forceinline__ uint4 ld_pair(const void* p) {
    unsigned long long a, b;
    asm volatile("{ .reg .b128 t; ld.relaxed.gpu.global.b128 t, [%2]; mov.b128 {%0, %1}, t; }" : "=l"(a), "=l"(b) : "l"(p) : "memory");
    return make_uint4((uint32_t)a, (uint32_t)(a >> 32), (uint32_t)b, (uint32_t)(b >> 32));
}
__device__ __forceinline__ void st_pair(void* p, uint4 v) {
    const unsigned long long a = ((unsigned long long)v.y << 32) | v.x, b = ((unsigned long long)v.w << 32) | v.z;
    asm volatile("{ .reg .b128 t; mov.b128 t, {%1, %2}; st.relaxed.gpu.global.b128 [%0], t; }" :: "l"(p), "l"(a), "l"(b) : "memory");
}
__device__ __forceinline__ int perm_col(int k) {
    const int j = k >> 3, p = k & 7;
    return (j >> 2) * 32 + (p >> 1) * 8 + (j & 3) * 2 + (p & 1);
}

__device__ __forceinline__ void wg_gemm(float (&d)[8][4], const uint32_t (&a)[16], uint32_t waddr, uint32_t accum) {
    const unsigned long long desc = (unsigned long long)((waddr & 0x3FFFFu) >> 4) | (1ull << 16) | (64ull << 32) | (1ull << 62);
    asm volatile("wgmma.fence.sync.aligned;" ::: "memory");
#pragma unroll
    for (int s = 0; s < 4; s++) {
        asm volatile("{ .reg .pred p; setp.ne.u32 p, %37, 0;"
                     " wgmma.mma_async.sync.aligned.m64n64k16.f32.bf16.bf16"
                     " {%0,%1,%2,%3,%4,%5,%6,%7,%8,%9,%10,%11,%12,%13,%14,%15,%16,%17,%18,%19,%20,%21,%22,%23,%24,%25,%26,%27,%28,%29,%30,%31},"
                     " {%32,%33,%34,%35}, %36, p, 1, 1, 1; }"
                     : "+f"(d[0][0]), "+f"(d[0][1]), "+f"(d[0][2]), "+f"(d[0][3]), "+f"(d[1][0]), "+f"(d[1][1]), "+f"(d[1][2]), "+f"(d[1][3]),
                       "+f"(d[2][0]), "+f"(d[2][1]), "+f"(d[2][2]), "+f"(d[2][3]), "+f"(d[3][0]), "+f"(d[3][1]), "+f"(d[3][2]), "+f"(d[3][3]),
                       "+f"(d[4][0]), "+f"(d[4][1]), "+f"(d[4][2]), "+f"(d[4][3]), "+f"(d[5][0]), "+f"(d[5][1]), "+f"(d[5][2]), "+f"(d[5][3]),
                       "+f"(d[6][0]), "+f"(d[6][1]), "+f"(d[6][2]), "+f"(d[6][3]), "+f"(d[7][0]), "+f"(d[7][1]), "+f"(d[7][2]), "+f"(d[7][3])
                     : "r"(a[4 * s]), "r"(a[4 * s + 1]), "r"(a[4 * s + 2]), "r"(a[4 * s + 3]), "l"(desc + s * 128), "r"(s ? 1u : accum)
                     : "memory");
    }
    asm volatile("wgmma.commit_group.sync.aligned;" ::: "memory");
    asm volatile("wgmma.wait_group.sync.aligned 0;"
                 : "+f"(d[0][0]), "+f"(d[0][1]), "+f"(d[0][2]), "+f"(d[0][3]), "+f"(d[1][0]), "+f"(d[1][1]), "+f"(d[1][2]), "+f"(d[1][3]),
                   "+f"(d[2][0]), "+f"(d[2][1]), "+f"(d[2][2]), "+f"(d[2][3]), "+f"(d[3][0]), "+f"(d[3][1]), "+f"(d[3][2]), "+f"(d[3][3]),
                   "+f"(d[4][0]), "+f"(d[4][1]), "+f"(d[4][2]), "+f"(d[4][3]), "+f"(d[5][0]), "+f"(d[5][1]), "+f"(d[5][2]), "+f"(d[5][3]),
                   "+f"(d[6][0]), "+f"(d[6][1]), "+f"(d[6][2]), "+f"(d[6][3]), "+f"(d[7][0]), "+f"(d[7][1]), "+f"(d[7][2]), "+f"(d[7][3])
                 :: "memory");
}
__device__ __forceinline__ void undef_acc(float (&d)[8][4]) {
#pragma unroll
    for (int j = 0; j < 8; j++) asm volatile("" : "=f"(d[j][0]), "=f"(d[j][1]), "=f"(d[j][2]), "=f"(d[j][3]));
}
__device__ __forceinline__ void zero_acc(float (&d)[8][4]) {
#pragma unroll
    for (int j = 0; j < 8; j++) { d[j][0] = 0.f; d[j][1] = 0.f; d[j][2] = 0.f; d[j][3] = 0.f; }
}
__device__ __forceinline__ void to_afrag(uint32_t (&a)[16], const float (&d)[8][4]) {
#pragma unroll
    for (int j = 0; j < 8; j++) {
        a[2 * j] = pack_bf16(d[j][0], d[j][1]);
        a[2 * j + 1] = pack_bf16(d[j][2], d[j][3]);
    }
}
__device__ __forceinline__ void to_afrag(uint32_t (&a)[16], const float (&d)[8][4], float s_lo, float s_hi) {
#pragma unroll
    for (int j = 0; j < 8; j++) {
        a[2 * j] = pack_bf16(d[j][0] * s_lo, d[j][1] * s_lo);
        a[2 * j + 1] = pack_bf16(d[j][2] * s_hi, d[j][3] * s_hi);
    }
}
__device__ __forceinline__ void ld_pair_if(uint4& v, const void* p, bool c) {
    unsigned long long a = ((unsigned long long)v.y << 32) | v.x, b = ((unsigned long long)v.w << 32) | v.z;
    asm volatile("{ .reg .pred p; .reg .b128 t; setp.ne.u32 p, %3, 0; mov.b128 t, {%0, %1}; @p ld.relaxed.gpu.global.b128 t, [%2]; mov.b128 {%0, %1}, t; }"
                 : "+l"(a), "+l"(b) : "l"(p), "r"((uint32_t)c) : "memory");
    v = make_uint4((uint32_t)a, (uint32_t)(a >> 32), (uint32_t)b, (uint32_t)(b >> 32));
}
__device__ __forceinline__ void load_own(uint4 (&xo)[4], const __nv_bfloat16* x, int tile, int lane) {
    const char* xr = reinterpret_cast<const char*>(x) + (size_t)(tile * 16 + (lane >> 2)) * 128 + (lane & 3) * 16;
    xo[0] = ldg_stream(xr);
    xo[1] = ldg_stream(xr + 64);
    xo[2] = ldg_stream(xr + 1024);
    xo[3] = ldg_stream(xr + 1024 + 64);
}
__device__ __forceinline__ void query_gemm(uint32_t (&tq)[16], const uint4 (&xo)[4], uint32_t sb) {
    const uint32_t xa[16] = {xo[0].x, xo[2].x, xo[0].y, xo[2].y, xo[0].z, xo[2].z, xo[0].w, xo[2].w,
                             xo[1].x, xo[3].x, xo[1].y, xo[3].y, xo[1].z, xo[3].z, xo[1].w, xo[3].w};
    float t[8][4];
    undef_acc(t);
    wg_gemm(t, xa, sb + SM_W, 0u);
    to_afrag(tq, t);
}

template <bool FIRST>
__device__ __forceinline__ void agg_chunk(float (&acc)[8][4], uint32_t la, int ofs, uint32_t a0, uint32_t a1, uint32_t a2, uint32_t a3) {
#pragma unroll
    for (int q = 0; q < 4; q++) {
        uint32_t b[4];
        ldsm4t(b, (la ^ (q << 5)) + ofs);
        if (FIRST) {
            mma16816_z(acc[2 * q], a0, a1, a2, a3, b[0], b[1]);
            mma16816_z(acc[2 * q + 1], a0, a1, a2, a3, b[2], b[3]);
        } else {
            mma16816(acc[2 * q], a0, a1, a2, a3, b[0], b[1]);
            mma16816(acc[2 * q + 1], a0, a1, a2, a3, b[2], b[3]);
        }
    }
}
__device__ __forceinline__ void issue_chunk(uint32_t da, int ofs, uint32_t ra, const char* xl) {
    const uint2 p = lds64(ra);
    const uint32_t db = da ^ 0x90u;
    cp16_row(da + ofs, xl, p.x & 0xFFFFu);
    cp16_row(db + ofs, xl, p.x >> 16);
    cp16_row(da + ofs + 1024, xl, p.y & 0xFFFFu);
    cp16_row(db + ofs + 1024, xl, p.y >> 16);
    cp_commit();
}
template <bool FIRST>
__device__ __forceinline__ void local_chunk(float (&acc)[8][4], uint32_t la, int ofs, uint32_t rt, uint32_t code) {
    const uint4 p = lds128(rt);
    const uint32_t w01 = prmt(p.x, p.y, 0x5410), w23 = prmt(p.z, p.w, 0x5410);
    const uint32_t r01 = prmt(p.x, p.y, 0x7632), r23 = prmt(p.z, p.w, 0x7632);
    agg_chunk<FIRST>(acc, la, ofs, w01 & eq_lo2(r01, code), w01 & eq_hi2(r01, code), w23 & eq_lo2(r23, code), w23 & eq_hi2(r23, code));
}
__device__ __forceinline__ void attn_chunk(uint32_t (&y)[16], float& d0, float& d1, const uint32_t (&tq)[16], uint32_t lb, int lane) {
    float s0[4], s1[4];
    uint32_t xe[16];
#pragma unroll
    for (int s = 0; s < 4; s++) {
        ldsm4(xe[4 * s], xe[4 * s + 2], xe[4 * s + 1], xe[4 * s + 3], lb ^ (s << 5));
        if (s == 0) {
            mma16816_z(s0, tq[0], tq[1], tq[2], tq[3], xe[0], xe[2]);
            mma16816_z(s1, tq[0], tq[1], tq[2], tq[3], xe[1], xe[3]);
        } else {
            mma16816(s0, tq[4 * s], tq[4 * s + 1], tq[4 * s + 2], tq[4 * s + 3], xe[4 * s], xe[4 * s + 2]);
            mma16816(s1, tq[4 * s], tq[4 * s + 1], tq[4 * s + 2], tq[4 * s + 3], xe[4 * s + 1], xe[4 * s + 3]);
        }
    }
    const bool odd = lane & 4;
    const float p0 = ex2(odd ? s0[1] : s0[0]), p1 = ex2(odd ? s1[3] : s1[2]);
    d0 += p0;
    d1 += p1;
    const uint32_t p = __shfl_sync(~0u, pack_bf16(p0, p1), (lane & 28) | (lane >> 3));
    const uint32_t q0 = prmt(p, p, 0x1010), q1 = prmt(p, p, 0x3232);
#pragma unroll
    for (int i = 0; i < 16; i++) y[i] = fma_bf2(xe[i], (i & 1) ? q1 : q0, y[i]);
}
__device__ __forceinline__ void finish(float (&acc)[8][4], const uint32_t (&ao)[16], uint32_t sb,
                                       __nv_bfloat16* out, int tile, int lane) {
    uint32_t af[16];
    const uint32_t pd = sb + SM_DIS + (threadIdx.x >> 5) * 32 + (lane >> 2) * 2;
    to_afrag(af, acc, __uint_as_float(lds16(pd) << 16), __uint_as_float(lds16(pd + 16) << 16));
    wg_gemm(acc, af, sb + SM_W + 8192, blockDim.y - 1u);
    to_afrag(af, acc);
#pragma unroll
    for (int i = 0; i < 16; i++) af[i] = add_bf2(af[i], ao[i]);
    if (tile < N_TILES) {
        char* orow = reinterpret_cast<char*>(out) + (size_t)(tile * 16 + (lane >> 2)) * 128 + (lane & 3) * 16;
        *reinterpret_cast<uint4*>(orow) = make_uint4(af[0], af[2], af[4], af[6]);
        *reinterpret_cast<uint4*>(orow + 64) = make_uint4(af[8], af[10], af[12], af[14]);
        *reinterpret_cast<uint4*>(orow + 1024) = make_uint4(af[1], af[3], af[5], af[7]);
        *reinterpret_cast<uint4*>(orow + 1024 + 64) = make_uint4(af[9], af[11], af[13], af[15]);
    }
}

__device__ __noinline__ void slow_cta(const __nv_bfloat16* x, const int* src, const int* dst, const int* esrc, const int* edst,
                                      const __nv_bfloat16* dis, __nv_bfloat16* out, unsigned char* smem) {
    constexpr int QCAP = 64;
    const int tid = threadIdx.x, lane = tid & 31, warp = tid >> 5, cta = blockIdx.x;
    const int tile = cta * NW + warp;
    float2* acc = reinterpret_cast<float2*>(smem + SM_STAGE + warp * 8192) + lane;
    float2* aux = acc + 512;
    uint32_t* queue = reinterpret_cast<uint32_t*>(smem + SM_STAGE + NW * 8192);
    uint32_t* cnt = queue + NW * QCAP;
    static_assert(SM_STAGE + NW * 8192 + NW * QCAP * 4 + NW * 4 <= SM_TOTAL, "slow path scratch");
    const uint32_t* xw = reinterpret_cast<const uint32_t*>(x) + lane;
    auto lo = [](uint32_t v) { return __uint_as_float(v << 16); };
    auto hi = [](uint32_t v) { return __uint_as_float(v & 0xFFFF0000u); };
    auto matvec = [&](float v0, float v1, int wofs, bool rows) {
        float2 r = make_float2(0.f, 0.f);
        const int c = rows ? lane : ((lane & 16) | ((lane & 3) << 2) | ((lane >> 2) & 3));
#pragma unroll 1
        for (int k = 0; k < 64; k++) {
            const int f = rows ? perm_col(k) : k;
            const float a = __shfl_sync(~0u, (f & 1) ? v1 : v0, f >> 1);
            const uint32_t w = *reinterpret_cast<const uint32_t*>(smem + wofs + k * 128 + (((c >> 2) ^ (k & 7)) << 4) + (c & 3) * 4);
            r.x += a * lo(w);
            r.y += a * hi(w);
        }
        return r;
    };
    cp_wait<0>();
    __syncthreads();
    if (tid < NW) cnt[tid] = 0u;
#pragma unroll 1
    for (int r = 0; r < 16; r++) {
        const uint32_t v = __ldg(xw + (size_t)(min(tile, N_TILES - 1) * 16 + r) * 32);
        aux[r * 32] = matvec(lo(v), hi(v), SM_W, true);
    }
    __syncthreads();
#pragma unroll 1
    for (int pass = 0; pass < 2; pass++) {
        const int* dl = pass ? dst : edst;
        const int* sl = pass ? src : esrc;
        const int ne = pass ? N_EDGES : N_XEDGES;
        float den = 0.f;
#pragma unroll 1
        for (int r = 0; r < 16; r++) acc[r * 32] = make_float2(0.f, 0.f);
        int dnext = __ldg(dl + tid);
#pragma unroll 1
        for (int e = tid; e - tid < ne; e += NT) {
            const uint32_t loc = (uint32_t)(dnext - cta * NPC);
            bool pend = e < ne && loc < (uint32_t)NPC;
            if (e + NT < ne) dnext = __ldg(dl + e + NT);
            int more;
            do {
                if (pend) {
                    const uint32_t pos = atomicAdd(cnt + (loc >> 4), 1u);
                    if (pos < (uint32_t)QCAP) { queue[(loc >> 4) * QCAP + pos] = (uint32_t)e * 16u + (loc & 15u); pend = false; }
                }
                more = __syncthreads_or(pend);
                if (more || e - tid + NT >= ne) {
                    const int n = min((int)cnt[warp], QCAP);
#pragma unroll 1
                    for (int c = 0; c < n; c++) {
                        const uint32_t q = queue[warp * QCAP + c], r = q & 15u;
                        const int s = __ldg(sl + (q >> 4));
                        const uint32_t v = __ldg(xw + (size_t)s * 32);
                        float w;
                        if (pass) {
                            w = __bfloat162float(dis[s]);
                        } else {
                            const float2 t = aux[r * 32];
                            w = t.x * lo(v) + t.y * hi(v);
#pragma unroll
                            for (int o = 16; o; o >>= 1) w += __shfl_xor_sync(~0u, w, o);
                            w = ex2(w);
                            if (lane == (int)r) den += w;
                        }
                        float2 a = acc[r * 32];
                        a.x += w * lo(v);
                        a.y += w * hi(v);
                        acc[r * 32] = a;
                    }
                    __syncwarp();
                    if (lane == 0) cnt[warp] = 0u;
                    __syncthreads();
                }
            } while (more);
        }
#pragma unroll 1
        for (int r = 0; r < 16; r++) {
            const int node = min(tile, N_TILES - 1) * 16 + r;
            const float sc = pass ? __bfloat162float(dis[node]) : 1.f / (__shfl_sync(~0u, den, r) + 1e-9f);
            const float2 a = acc[r * 32];
            const float2 o = matvec(a.x * sc, a.y * sc, SM_W + (pass ? 8192 : 2 * 8192), false);
            if (pass == 0) aux[r * 32] = o;
            else if (tile < N_TILES) reinterpret_cast<uint32_t*>(out)[node * 32 + lane] = pack_bf16(o.x + aux[r * 32].x, o.y + aux[r * 32].y);
        }
    }
}

__device__ __forceinline__ void post1(uint32_t d, uint32_t s, uint32_t sb) {
    const uint32_t b = __umulhi(d, 11184811u), rk = atoms_add(sb + SM_HIST + b * 4, 4u);
    const uint32_t r = __umulhi(s, (uint32_t)(((unsigned long long)NRANGE << 32) / N_NODES));
    sts32(sb + SM_MB + b * MBS + min(rk, (uint32_t)(MBS - 4)), prmt(s, (r - b) * NPC + d, 0x5410));
}
__device__ __forceinline__ void post4(const uint4& dv, const uint4& sv, uint32_t sb) {
    const uint32_t d[4] = {dv.x, dv.y, dv.z, dv.w}, s[4] = {sv.x, sv.y, sv.z, sv.w};
    uint32_t b[4], rk[4];
#pragma unroll
    for (int i = 0; i < 4; i++) {
        b[i] = __umulhi(d[i], 11184811u);
        rk[i] = atoms_add(sb + SM_HIST + b[i] * 4, 4u);
    }
#pragma unroll
    for (int i = 0; i < 4; i++) {
        const uint32_t r = __umulhi(s[i], (uint32_t)(((unsigned long long)NRANGE << 32) / N_NODES));
        sts32(sb + SM_MB + b[i] * MBS + min(rk[i], (uint32_t)(MBS - 4)), prmt(s[i], (r - b[i]) * NPC + d[i], 0x5410));
    }
}

template <int MODE>
__global__ void __launch_bounds__(NT, 1)
exphormer_kernel(const __nv_bfloat16* __restrict__ x, const int* __restrict__ src, const int* __restrict__ dst,
                 const int* __restrict__ esrc, const int* __restrict__ edst, const __nv_bfloat16* __restrict__ dis,
                 const __nv_bfloat16* __restrict__ wl, const __nv_bfloat16* __restrict__ wq,
                 const __nv_bfloat16* __restrict__ wk, const __nv_bfloat16* __restrict__ wv,
                 __nv_bfloat16* __restrict__ out) {
    extern __shared__ __align__(1024) unsigned char smem[];
    const uint32_t sb = (uint32_t)__cvta_generic_to_shared(smem);
    const int tid = threadIdx.x, lane = tid & 31, warp = tid >> 5, cta = blockIdx.x;
    const int tile = cta * NW + warp;
    const int tl = min(tile, N_TILES - 1);
    const int c6 = tid / 6, k6 = tid - c6 * 6;
    PROF(0);

    const bool prod = MODE != 2 && cta < NPROD;
    const int nown = min(NPC, N_NODES - cta * NPC);
    uint32_t ep = 0;
    if (tid == NT - 32) {
        if (MODE != 1) {
            const uint32_t mbar = sb + SM_MISC;
            asm volatile("mbarrier.init.shared.b64 [%0], 1;" :: "r"(mbar) : "memory");
            fence_async();
            asm volatile("mbarrier.arrive.expect_tx.shared.b64 _, [%0], %1;" :: "r"(mbar), "r"(N_NODES * 2 + nown * 2) : "memory");
            asm volatile("cp.async.bulk.shared::cluster.global.mbarrier::complete_tx::bytes [%0], [%1], %2, [%3];"
                         :: "r"(sb + SM_TABLE), "l"(dis), "r"(TAB0), "r"(mbar) : "memory");
            asm volatile("cp.async.bulk.shared::cluster.global.mbarrier::complete_tx::bytes [%0], [%1], %2, [%3];"
                         :: "r"(sb + SM_DIS), "l"(dis + cta * NPC), "r"(nown * 2), "r"(mbar) : "memory");
        }
        asm volatile("ld.relaxed.gpu.global.u32 %0, [%1];" : "=r"(ep) : "l"(g_epoch + cta) : "memory");
    }
    const uint32_t wd = sb + SM_W + 8192 + (tid >> 1) * 128 + ((((tid & 1) * 4) ^ ((tid >> 1) & 7)) << 4);
    if (MODE != 1) {
        if (warp >= 8) {
            const int i = tid - 256, r = i >> 3;
            const uint32_t d = sb + SM_WQK + r * 128 + (((i ^ r) & 7) << 4);
            cp16(d, wq + perm_col(r) * 64 + (i & 7) * 8);
            cp16(d + 8192, wk + i * 8);
        } else {
            const char* pa = reinterpret_cast<const char*>(warp < 4 ? wl : wv) + (tid & 127) * 64;
#pragma unroll
            for (int q = 0; q < 4; q++) cp16(wd ^ (q << 4), pa + q * 16);
        }
    }
    cp_commit();
    const uint32_t chk = (uint32_t)min(cta * NCHK + NT - 1 - tid, N_NODES - 1);
    const uint32_t ea = sb + SM_WR + tid * 16, xa = sb + SM_WR + 4 * NT * 16 + tid * 8;
    const uint32_t ca = sb + SM_WQK + 2 * 8192 + (tid - (NT - NCHK)) * 16;
    if (prod) {
        const int eo = cta * EC + tid * 4;
        if (tid < EX) {
            cp4(xa, dst + NPROD * EC + cta * EX + tid);
            cp4(xa + 4, src + NPROD * EC + cta * EX + tid);
        }
        cp16(ea, dst + eo);
        cp16(ea + NT * 16, src + eo);
        cp_commit();
        cp16(ea + 2 * NT * 16, dst + eo + NT * 4);
        cp16(ea + 3 * NT * 16, src + eo + NT * 4);
        if (tid >= NT - NCHK) cp16(ca, edst + chk * 4);
    } else {
        cp_commit();
    }
    cp_commit();
    PROF(21);
    {
        const uint32_t nul = 0xFFFFu | (uint32_t)(NKEY + ((cta * 6 + k6) & 31)) << 20;
#pragma unroll
        for (int i = 0; i < STG / (NT * 16); i++) sts128(sb + SM_MB + tid * 16 + i * NT * 16, nul);
    }
    if (tid < (SM_MISC - SM_HIST) / 4) sts32(sb + SM_HIST + tid * 4, 0u);
    PROF(22);
    cp_wait<2>();
    __syncthreads();
    PROF(1);
    if (tid == NT - 32) {
        ep = ep % 7u + 1u;
        sts32(sb + SM_MISC + 8, ep << 29);
        if (MODE != 1) g_epoch[cta] = ep;
    }
    if (MODE != 1) {
        if (warp >= 8) {
            const int mi = (warp - 8) >> 2, jp = warp & 3;
            const uint32_t pa = sb + SM_WQK + (mi * 16 + (lane & 15)) * 128 + (((lane >> 4) ^ (lane & 7)) << 4);
            const uint32_t pb = sb + SM_WQK + 8192 + (jp * 16 + (lane & 7) + (lane >> 4) * 8) * 128 + ((((lane >> 3) & 1) ^ (lane & 7)) << 4);
            float d0[4], d1[4];
#pragma unroll
            for (int s = 0; s < 4; s++) {
                uint32_t a[4], b[4];
                ldsm4(a[0], a[1], a[2], a[3], pa ^ (s << 5));
                ldsm4(b[0], b[1], b[2], b[3], pb ^ (s << 5));
                if (s == 0) { mma16816_z(d0, a[0], a[1], a[2], a[3], b[0], b[1]); mma16816_z(d1, a[0], a[1], a[2], a[3], b[2], b[3]); }
                else        { mma16816(d0, a[0], a[1], a[2], a[3], b[0], b[1]);   mma16816(d1, a[0], a[1], a[2], a[3], b[2], b[3]); }
            }
            const float sc = 0.125f * 1.4426950408889634f;
            stsm4(sb + SM_W + (mi * 16 + (lane & 15)) * 128 + (((jp * 2 + (lane >> 4)) ^ (lane & 7)) << 4),
                  pack_bf16(d0[0] * sc, d0[1] * sc), pack_bf16(d0[2] * sc, d0[3] * sc),
                  pack_bf16(d1[0] * sc, d1[1] * sc), pack_bf16(d1[2] * sc, d1[3] * sc));
        } else {
            const uint4 a = lds128(wd), b = lds128(wd ^ 16), c = lds128(wd ^ 32), d = lds128(wd ^ 48);
            sts128v(wd, a.x, b.x, c.x, d.x);
            sts128v(wd ^ 16, a.y, b.y, c.y, d.y);
            sts128v(wd ^ 32, a.z, b.z, c.z, d.z);
            sts128v(wd ^ 48, a.w, b.w, c.w, d.w);
        }
    }
    PROF(2);
    bool irr = false;
    cp_wait<1>();
    PROF(16);
    if (MODE != 1 && tid == NT - 32) {
        asm volatile("cp.async.bulk.prefetch.L2.global [%0], %1;" :: "l"(esrc + cta * NPC * 4), "r"(nown * 16) : "memory");
        asm volatile("cp.async.bulk.prefetch.L2.global [%0], %1;" :: "l"(x + (size_t)cta * NPC * 64), "r"(nown * 128) : "memory");
    }
    if (prod) {
        if (tid < EX) { const uint2 e = lds64(xa); post1(e.x, e.y, sb); }
        post4(lds128(ea), lds128(ea + NT * 16), sb);
        PROF(3);
        cp_wait<0>();
        PROF(17);
        post4(lds128(ea + 2 * NT * 16), lds128(ea + 3 * NT * 16), sb);
        if (tid >= NT - NCHK) {
            const uint4 ed = lds128(ca);
            irr = ed.x != chk || ed.y != chk || ed.z != chk || ed.w != chk;
        }
    }
    fence_async();
    PROF(4);
    irr = __syncthreads_or(irr);
    PROF(5);
    const uint32_t tagw = lds32(sb + SM_MISC + 8);
    if (prod) {
#pragma unroll 1
        for (int c = c6; c < NCTA; c += NPROD) {
            const uint32_t n4 = lds32(sb + SM_HIST + c * 4);
            const uint32_t sa = sb + SM_MB + c * MBS + k6 * 16;
            uint4 v0 = lds128(sa), v1 = lds128(sa + 96), v2, v3;
            const bool bad = irr || n4 >= (uint32_t)MBS;
            const int code = bad ? 0 : (int)(max(n4, 192u) - 192u + 31u) >> 5;
            const bool p2 = (k6 >> 1) < code, p3 = (k6 >> 1) + 3 < code;
            if (p2) v2 = lds128(sa + 192);
            if (p3) v3 = lds128(sa + 288);
            v0.x |= tagw; v1.x |= tagw; v2.x |= tagw; v3.x |= tagw;
            v0.y |= (uint32_t)(bad ? 7 : code) << 29;
            unsigned char* ga = g_rec + c * GBKT + cta * 96 + k6 * 16;
            st_pair(ga, v0);
            st_pair(ga + GBLK, v1);
            if (p2) st_pair(ga + 2 * GBLK, v2);
            if (p3) st_pair(ga + 3 * GBLK, v3);
        }
    }
    PROF(6);
    if (MODE == 1) return;
    const uint2 es = ldg64(esrc + tl * 64 + lane * 2);
    if (tid == NT - 32)
        asm volatile("cp.async.bulk.shared::cluster.global.mbarrier::complete_tx::bytes [%0], [%1], %2, [%3];"
                     :: "r"(sb + SM_WQK), "l"(dis + TAB0 / 2), "r"(N_NODES * 2 - TAB0), "r"(sb + SM_MISC) : "memory");
#pragma unroll
    for (int i = 0; i < (NFILL + NT - 1) / NT; i++)
        if ((i + 1) * NT <= NFILL || tid + i * NT < NFILL) sts128(ea + i * NT * 16, ~0u);

    const char* xl = reinterpret_cast<const char*>(x) + (lane & 7) * 16;
    const uint32_t st0 = sb + SM_STAGE + warp * 2048;
    const uint32_t da = st0 + (lane >> 3) * 256 + (((lane & 7) ^ ((lane >> 3) * 2)) << 4);
    const uint32_t al = sb + SM_AL + warp * 128 + (lane >> 3) * 8;
    uint4 xo[4];
    {
        const uint32_t aa = sb + SM_AL + warp * 128 + (lane & 1) * 64 + (lane & 12) * 2 + (lane & 2) + (lane >> 4) * 4;
        sts16(aa, es.x);
        sts16(aa + 32, es.y);
    }
    PROF(18);
    __syncthreads();
    issue_chunk(da, 0, al, xl);
    PROF(19);

    uint32_t nch;
    {
        unsigned char* gp = g_rec + cta * GBKT + tid * 16;
        const uint32_t nul = 0xFFFFu | (uint32_t)(NKEY + lane) << 20;
        uint4 r0, r1, r2 = make_uint4(nul | tagw, nul, nul, nul), r3 = r2;
        int it = 0;
#pragma unroll 1
        do {
            r0 = ld_pair(gp);
            r1 = ld_pair(gp + GBLK);
            if (++it > (1 << 22)) __trap();
        } while (__any_sync(~0u, ((r0.x ^ tagw) | (r1.x ^ tagw)) >> 29));
        PROF(7);
        int code = r0.y >> 29;
        const bool abn = code == 7;
        code = abn ? 0 : code;
        const bool p2 = (k6 >> 1) < code, p3 = (k6 >> 1) + 3 < code;
        ld_pair_if(r2, gp + 2 * GBLK, p2);
        {
            uint32_t ok;
            do {
                asm volatile("{ .reg .pred p; mbarrier.try_wait.parity.shared.b64 p, [%1], 0; selp.u32 %0, 1, 0, p; }"
                             : "=r"(ok) : "r"(sb + SM_MISC) : "memory");
                if (++it > (1 << 22)) __trap();
            } while (!ok);
        }
        uint4 w0, w1, w2, w3;
        count4(w0, r0, sb);
        count4(w1, r1, sb);
        load_own(xo, x, tl, lane);
        const bool rare = __any_sync(~0u, p3 || ((r2.x ^ tagw) >> 29));
        if (rare) {
#pragma unroll 1
            do {
                ld_pair_if(r2, gp + 2 * GBLK, p2);
                ld_pair_if(r3, gp + 3 * GBLK, p3);
                if (++it > (1 << 22)) __trap();
            } while (((r2.x ^ tagw) | (r3.x ^ tagw)) >> 29);
            if (p3) st_pair(gp + 3 * GBLK, make_uint4(0u, 0u, 0u, 0u));
            count4(w3, r3, sb);
        }
        count4(w2, r2, sb);
        if (p2) st_pair(gp + 2 * GBLK, make_uint4(0u, 0u, 0u, 0u));
        PROF(8);
        __syncthreads();
        PROF(9);
        {
            issue_chunk(da, STG, al + 32, xl);
            issue_chunk(da, 2 * STG, al + 64, xl);
            const uint32_t ca = sb + SM_CNT + lane * (NW * 4) + warp * 4;
            uint32_t c = 0, v = 0;
            if (lane < NRANGE) { c = lds32(ca) * 4u; v = c * 0x10001u + (lane << 22); }
#pragma unroll
            for (int o = 1; o < 32; o <<= 1) {
                const uint32_t u = __shfl_up_sync(~0u, v, o);
                if (lane >= o) v = __viaddmax_u16x2(u, prmt(v, v, 0x1010), v);
            }
            if (lane < NRANGE) sts32(ca, (v >> 16) - c + sb + SM_WR + warp * (CAPR * 4));
            nch = (__reduce_max_sync(~0u, v) + (63u << 16)) >> 22;
        }
        if (__builtin_expect(__syncthreads_or(abn || nch > CAPR / 16), 0)) {
            slow_cta(x, src, dst, esrc, edst, dis, out, smem);
            return;
        }
        PROF(10);
        place4(r0, w0, sb);
        place4(r1, w1, sb);
        place4(r2, w2, sb);
        if (rare) place4(r3, w3, sb);
    }
    PROF(11);

    uint32_t ra = sb + SM_S16 + warp * (CAPR * 2) + (lane >> 3) * 8;
    uint32_t ao[16], rden;
    {
        uint32_t tq[16], y[16];
        float d0 = 0.f, d1 = 0.f;
        query_gemm(tq, xo, sb);
#pragma unroll
        for (int i = 0; i < 16; i++) y[i] = 0u;
        __syncthreads();
        PROF(12);
        const uint32_t lb = st0 + ((lane & 7) + (lane >> 4) * 8) * 128 + ((((lane >> 3) & 1) ^ (lane & 7)) << 4);
        uint32_t nxt = al + 96, so = 0;
#pragma unroll 1
        for (int j = 0; j < 4; j++) {
            cp_wait<2>(); wsync();
            attn_chunk(y, d0, d1, tq, lb + so, lane);
            wsync();
            issue_chunk(da + so, 0, nxt, xl);
            nxt = ra + j * 32;
            so = j == 2 ? 0 : so + STG;
        }
        rden = __shfl_sync(~0u, pack_bf16(__fdividef(1.f, d0 + 1e-9f), __fdividef(1.f, d1 + 1e-9f)), (lane & 28) | (lane >> 3));
        float t[8][4];
        undef_acc(t);
        wg_gemm(t, y, sb + SM_W + 2 * 8192, 0u);
        to_afrag(ao, t);
#pragma unroll
        for (int i = 0; i < 16; i++) asm volatile("" : "+r"(ao[i]));
        if (blockDim.z != 1) __trap();
    }
    PROF(13);

    float acc[8][4];
    {
        const uint32_t la = st0 + (lane & 15) * 128 + (((lane >> 4) ^ (lane & 7)) << 4);
        const uint32_t code = (uint32_t)(lane >> 2) * 0x10001u + 0x80000u;
        uint32_t rt = sb + SM_WR + warp * (CAPR * 4) + (lane & 3) * 16;
        int left = (int)nch;
#define STEP(OFS, NXT, K)                                        \
        wsync();                                                 \
        issue_chunk(da, OFS, ra + 96 + (K) * 32, xl);            \
        cp_wait<2>(); wsync();                                   \
        local_chunk<false>(acc, la, NXT, rt + 64 + (K) * 64, code);
        cp_wait<2>(); wsync();
        local_chunk<true>(acc, la, STG, rt, code);
#pragma unroll 1
        while (true) {
            STEP(STG, 2 * STG, 0)
            if (left == 2) break;
            STEP(2 * STG, 0, 1)
            if (left == 3) break;
            STEP(0, STG, 2)
            if (left == 4) break;
            left -= 3; rt += 192; ra += 96;
        }
#undef STEP
    }
    PROF(14);
    {
        const uint32_t q0 = prmt(rden, rden, 0x1010), q1 = prmt(rden, rden, 0x3232);
#pragma unroll
        for (int i = 0; i < 16; i++) ao[i] = mul_bf2(ao[i], (i & 1) ? q1 : q0);
        if (gridDim.y != 1) __trap();
    }
    finish(acc, ao, sb, out, tile, lane);
    cp_wait<0>();
    PROF(15);
}

}

extern "C" void kernel_launch(void* const* d_in, const int* in_sizes, int n_in, void* d_out, int out_size) {
    (void)in_sizes; (void)n_in; (void)out_size;
    const __nv_bfloat16* x   = (const __nv_bfloat16*)d_in[0];
    const int* src           = (const int*)d_in[1];
    const int* dst           = (const int*)d_in[2];
    const int* esrc          = (const int*)d_in[3];
    const int* edst          = (const int*)d_in[4];
    const __nv_bfloat16* dis = (const __nv_bfloat16*)d_in[5];
    const __nv_bfloat16* wl  = (const __nv_bfloat16*)d_in[6];
    const __nv_bfloat16* wq  = (const __nv_bfloat16*)d_in[7];
    const __nv_bfloat16* wk  = (const __nv_bfloat16*)d_in[8];
    const __nv_bfloat16* wv  = (const __nv_bfloat16*)d_in[9];
    __nv_bfloat16* out = (__nv_bfloat16*)d_out;

    static int fused = -1;
    if (fused < 0) {
        cudaFuncSetAttribute(exphormer_kernel<0>, cudaFuncAttributeMaxDynamicSharedMemorySize, SM_TOTAL);
        cudaFuncSetAttribute(exphormer_kernel<1>, cudaFuncAttributeMaxDynamicSharedMemorySize, SM_TOTAL);
        cudaFuncSetAttribute(exphormer_kernel<2>, cudaFuncAttributeMaxDynamicSharedMemorySize, SM_TOTAL);
        int dev = 0, sms = 0, occ = 0;
        cudaGetDevice(&dev);
        cudaDeviceGetAttribute(&sms, cudaDevAttrMultiProcessorCount, dev);
        cudaOccupancyMaxActiveBlocksPerMultiprocessor(&occ, exphormer_kernel<0>, NT, SM_TOTAL);
        fused = (sms * occ >= NCTA) ? 1 : 0;
    }
    if (fused) {
        exphormer_kernel<0><<<NCTA, NT, SM_TOTAL>>>(x, src, dst, esrc, edst, dis, wl, wq, wk, wv, out);
    } else {
        exphormer_kernel<1><<<NCTA, NT, SM_TOTAL>>>(x, src, dst, esrc, edst, dis, wl, wq, wk, wv, out);
        exphormer_kernel<2><<<NCTA, NT, SM_TOTAL>>>(x, src, dst, esrc, edst, dis, wl, wq, wk, wv, out);
    }
}
```

```cpp
#include <cuda_runtime.h>
#include <cuda_bf16.h>
#include <stdint.h>

namespace {

constexpr int N_NODES  = 50000;
constexpr int N_EDGES  = 800000;
constexpr int N_XEDGES = 200000;
constexpr int N_TILES  = N_NODES / 16;
constexpr int NW       = 24;
constexpr int NT       = NW * 32;
constexpr int NPC      = NW * 16;
constexpr int NCTA     = (N_NODES + NPC - 1) / NPC;
constexpr int NPROD    = NT / 6;
constexpr int EC       = NT * 8;
constexpr int EX       = N_EDGES / NPROD - EC;
constexpr int NMB      = (NCTA + 1) / 2;
constexpr int MBS      = 368;
constexpr int GOD      = NPROD * 192;
constexpr int GBKT     = NPROD * 384;
constexpr int BS       = 80;
constexpr int KDUM     = 416;
constexpr int KOFS     = 2048;
constexpr int TCAP     = 96;
#define PFT 352
constexpr int STG      = NW * 2048;

static_assert(NPROD * (EC + EX) == N_EDGES && EX <= NT && NPROD <= NCTA && N_NODES % 16 == 0, "edge slices");

constexpr int SM_W     = 0;
constexpr int SM_ES    = 3 * 8192;
constexpr int SM_DIS   = SM_ES + NPC * 16;
constexpr int SM_HIST  = SM_DIS + NPC * 2;
constexpr int SM_CNT   = SM_HIST + 2 * NMB * 4;
constexpr int SM_MISC  = SM_CNT + (KDUM + 32 + 4) * 4;
constexpr int SM_TAG   = SM_MISC + 40;
constexpr int SM_STAGE = 83200;
constexpr int SM_MB    = SM_STAGE;
constexpr int SM_TABLE = SM_STAGE + STG;
constexpr int SM_EXT   = SM_TABLE;
constexpr int SM_BIN   = SM_EXT - 64 - (128 - BS) * KOFS;
constexpr int SM_DUMP  = SM_BIN + NPC * BS;
constexpr int SM_TW    = SM_DUMP + 1536;
constexpr int SM_TS    = SM_TW + NW * TCAP * 4;
constexpr int SM_FLAG  = SM_TS + NW * TCAP * 2 + 128;
constexpr int SM_TOTAL = SM_TABLE + N_NODES * 2;
constexpr int SM_EDGE  = SM_BIN;
constexpr uint32_t sb  = 1024;
static_assert(SM_MISC % 8 == 0 && SM_TAG + 4 <= SM_BIN && SM_BIN % 16 == 0 && SM_STAGE % 256 == 0, "layout");
static_assert(SM_FLAG + NCTA * 16 <= SM_STAGE && SM_EDGE + EC * 8 <= SM_STAGE && 2 * NMB * MBS <= STG, "layout");
static_assert(SM_TOTAL <= 232448 && 2 * STG <= N_NODES * 2 && SM_TW <= SM_BIN + KDUM * BS + 64, "layout");
static_assert(SM_EXT + STG + NPROD * MBS <= SM_TOTAL && (SM_MISC - SM_HIST) / 4 <= NT, "cursor overrun stays inside");

__device__ __align__(128) unsigned char g_rec[2 * NMB * GBKT];
__device__ __align__(128) uint4 g_flag[NCTA * 2];
__device__ uint32_t g_count;

#define PROF(i) do {} while (0)

__device__ __forceinline__ void mma16816(float (&d)[4], uint32_t a0, uint32_t a1, uint32_t a2, uint32_t a3,
                                         uint32_t b0, uint32_t b1) {
    asm volatile("mma.sync.aligned.m16n8k16.row.col.f32.bf16.bf16.f32 {%0,%1,%2,%3}, {%4,%5,%6,%7}, {%8,%9}, {%0,%1,%2,%3};"
                 : "+f"(d[0]), "+f"(d[1]), "+f"(d[2]), "+f"(d[3])
                 : "r"(a0), "r"(a1), "r"(a2), "r"(a3), "r"(b0), "r"(b1));
}
__device__ __forceinline__ void mma16816_z(float (&d)[4], uint32_t a0, uint32_t a1, uint32_t a2, uint32_t a3,
                                           uint32_t b0, uint32_t b1) {
    asm volatile("mma.sync.aligned.m16n8k16.row.col.f32.bf16.bf16.f32 {%0,%1,%2,%3}, {%4,%5,%6,%7}, {%8,%9}, {%10,%10,%10,%10};"
                 : "=f"(d[0]), "=f"(d[1]), "=f"(d[2]), "=f"(d[3])
                 : "r"(a0), "r"(a1), "r"(a2), "r"(a3), "r"(b0), "r"(b1), "f"(0.f));
}
__device__ __forceinline__ void ldsm4(uint32_t& r0, uint32_t& r1, uint32_t& r2, uint32_t& r3, uint32_t addr) {
    asm volatile("ldmatrix.sync.aligned.m8n8.x4.shared.b16 {%0,%1,%2,%3}, [%4];"
                 : "=r"(r0), "=r"(r1), "=r"(r2), "=r"(r3) : "r"(addr) : "memory");
}
__device__ __forceinline__ void ldsm4t(uint32_t (&r)[4], uint32_t addr) {
    asm volatile("ldmatrix.sync.aligned.m8n8.x4.trans.shared.b16 {%0,%1,%2,%3}, [%4];"
                 : "=r"(r[0]), "=r"(r[1]), "=r"(r[2]), "=r"(r[3]) : "r"(addr) : "memory");
}
__device__ __forceinline__ void stsm4(uint32_t addr, uint32_t r0, uint32_t r1, uint32_t r2, uint32_t r3) {
    asm volatile("stmatrix.sync.aligned.m8n8.x4.shared.b16 [%0], {%1,%2,%3,%4};"
                 :: "r"(addr), "r"(r0), "r"(r1), "r"(r2), "r"(r3) : "memory");
}
__device__ __forceinline__ uint32_t pack_bf16(float lo, float hi) {
    uint32_t r;
    asm("cvt.rn.bf16x2.f32 %0, %1, %2;" : "=r"(r) : "f"(hi), "f"(lo));
    return r;
}
__device__ __forceinline__ uint32_t fma_bf2(uint32_t a, uint32_t b, uint32_t c) {
    uint32_t r;
    asm volatile("fma.rn.bf16x2 %0, %1, %2, %3;" : "=r"(r) : "r"(a), "r"(b), "r"(c));
    return r;
}
__device__ __forceinline__ uint32_t mul_bf2(uint32_t a, uint32_t b) {
    uint32_t r;
    asm volatile("mul.rn.bf16x2 %0, %1, %2;" : "=r"(r) : "r"(a), "r"(b));
    return r;
}
__device__ __forceinline__ uint32_t add_bf2(uint32_t a, uint32_t b) {
    uint32_t r;
    asm("add.rn.bf16x2 %0, %1, %2;" : "=r"(r) : "r"(a), "r"(b));
    return r;
}
__device__ __forceinline__ uint32_t prmt(uint32_t a, uint32_t b, uint32_t s) {
    uint32_t r;
    asm("prmt.b32 %0, %1, %2, %3;" : "=r"(r) : "r"(a), "r"(b), "r"(s));
    return r;
}
__device__ __forceinline__ uint32_t eq_lo2(uint32_t a, uint32_t b) {
    uint32_t r;
    asm("{ .reg .b16 l, h; .reg .b32 c; mov.b32 {l, h}, %2; mov.b32 c, {l, l}; set.eq.u32.f16x2 %0, %1, c; }" : "=r"(r) : "r"(a), "r"(b));
    return r;
}
__device__ __forceinline__ uint32_t eq_hi2(uint32_t a, uint32_t b) {
    uint32_t r;
    asm("{ .reg .b16 l, h; .reg .b32 c; mov.b32 {l, h}, %2; mov.b32 c, {h, h}; set.eq.u32.f16x2 %0, %1, c; }" : "=r"(r) : "r"(a), "r"(b));
    return r;
}
__device__ __forceinline__ float ex2(float x) {
    float r;
    asm("ex2.approx.ftz.f32 %0, %1;" : "=f"(r) : "f"(x));
    return r;
}
__device__ __forceinline__ void cp16(uint32_t dst, const void* src) {
    asm volatile("cp.async.cg.shared.global [%0], [%1], 16;" :: "r"(dst), "l"(src) : "memory");
}
__device__ __forceinline__ void cp4(uint32_t dst, const void* src) {
    asm volatile("cp.async.ca.shared.global [%0], [%1], 4;" :: "r"(dst), "l"(src) : "memory");
}
__device__ __forceinline__ void cp16_row(uint32_t dst, const char* xl, uint32_t s) {
    asm volatile("{ .reg .pred p; .reg .b64 a; setp.ne.u32 p, %2, 0xFFFF; mad.wide.u32 a, %2, 128, %1; @p cp.async.cg.shared.global [%0], [a], 16; }"
                 :: "r"(dst), "l"(xl), "r"(s) : "memory");
}
__device__ __forceinline__ void cp_commit() { asm volatile("cp.async.commit_group;" ::: "memory"); }
template <int N> __device__ __forceinline__ void cp_wait() { asm volatile("cp.async.wait_group %0;" :: "n"(N) : "memory"); }
__device__ __forceinline__ void fence_async() { asm volatile("fence.proxy.async.shared::cta;" ::: "memory"); }
__device__ __forceinline__ void wsync() { asm volatile("bar.warp.sync 0xffffffff;" ::: "memory"); }
__device__ __forceinline__ uint4 ldg_stream(const void* p) {
    uint4 v;
    asm volatile("ld.global.L1::no_allocate.v4.u32 {%0,%1,%2,%3}, [%4];" : "=r"(v.x), "=r"(v.y), "=r"(v.z), "=r"(v.w) : "l"(p) : "memory");
    return v;
}
__device__ __forceinline__ uint2 ldg64(const void* p) {
    uint2 v;
    asm volatile("ld.global.L1::no_allocate.v2.u32 {%0,%1}, [%2];" : "=r"(v.x), "=r"(v.y) : "l"(p) : "memory");
    return v;
}
__device__ __forceinline__ uint4 lds128(uint32_t a) {
    uint4 v;
    asm volatile("ld.shared.v4.u32 {%0,%1,%2,%3}, [%4];" : "=r"(v.x), "=r"(v.y), "=r"(v.z), "=r"(v.w) : "r"(a) : "memory");
    return v;
}
__device__ __forceinline__ uint2 lds64(uint32_t a) {
    uint2 v;
    asm volatile("ld.shared.v2.u32 {%0,%1}, [%2];" : "=r"(v.x), "=r"(v.y) : "r"(a) : "memory");
    return v;
}
__device__ __forceinline__ uint32_t lds32(uint32_t a) {
    uint32_t v;
    asm volatile("ld.shared.u32 %0, [%1];" : "=r"(v) : "r"(a) : "memory");
    return v;
}
__device__ __forceinline__ uint32_t lds16(uint32_t a) {
    uint32_t v;
    asm volatile("ld.shared.u16 %0, [%1];" : "=r"(v) : "r"(a) : "memory");
    return v;
}
__device__ __forceinline__ void sts16(uint32_t a, uint32_t v) { asm volatile("st.shared.u16 [%0], %1;" :: "r"(a), "r"(v) : "memory"); }
__device__ __forceinline__ void sts32(uint32_t a, uint32_t v) { asm volatile("st.shared.u32 [%0], %1;" :: "r"(a), "r"(v) : "memory"); }
__device__ __forceinline__ void sts64(uint32_t a, uint32_t x, uint32_t y) {
    asm volatile("st.shared.v2.u32 [%0], {%1,%2};" :: "r"(a), "r"(x), "r"(y) : "memory");
}
__device__ __forceinline__ void sts128(uint32_t a, uint32_t v) {
    asm volatile("st.shared.v4.u32 [%0], {%1,%1,%1,%1};" :: "r"(a), "r"(v) : "memory");
}
__device__ __forceinline__ uint32_t atoms_add(uint32_t a, uint32_t v) {
    uint32_t r;
    asm volatile("atom.shared.add.u32 %0, [%1], %2;" : "=r"(r) : "r"(a), "r"(v) : "memory");
    return r;
}
__device__ __forceinline__ void sts128v(uint32_t a, uint32_t x, uint32_t y, uint32_t z, uint32_t w) {
    asm volatile("st.shared.v4.u32 [%0], {%1,%2,%3,%4};" :: "r"(a), "r"(x), "r"(y), "r"(z), "r"(w) : "memory");
}
__device__ __forceinline__ uint4 ldg128(const void* p) {
    uint4 v;
    asm volatile("ld.global.v4.u32 {%0,%1,%2,%3}, [%4];" : "=r"(v.x), "=r"(v.y), "=r"(v.z), "=r"(v.w) : "l"(p) : "memory");
    return v;
}
__device__ __forceinline__ uint32_t ldg32(const void* p) {
    uint32_t v;
    asm volatile("ld.global.L1::no_allocate.u32 %0, [%1];" : "=r"(v) : "l"(p) : "memory");
    return v;
}
__device__ __forceinline__ uint4 ld_pair(const void* p) {
    unsigned long long a, b;
    asm volatile("{ .reg .b128 t; ld.relaxed.gpu.global.b128 t, [%2]; mov.b128 {%0, %1}, t; }" : "=l"(a), "=l"(b) : "l"(p) : "memory");
    return make_uint4((uint32_t)a, (uint32_t)(a >> 32), (uint32_t)b, (uint32_t)(b >> 32));
}
__device__ __forceinline__ void st_pair(void* p, uint4 v) {
    const unsigned long long a = ((unsigned long long)v.y << 32) | v.x, b = ((unsigned long long)v.w << 32) | v.z;
    asm volatile("{ .reg .b128 t; mov.b128 t, {%1, %2}; st.relaxed.gpu.global.b128 [%0], t; }" :: "l"(p), "l"(a), "l"(b) : "memory");
}
__device__ __forceinline__ int perm_col(int k) {
    const int j = k >> 3, p = k & 7;
    return (j >> 2) * 32 + (p >> 1) * 8 + (j & 3) * 2 + (p & 1);
}

__device__ __forceinline__ void wg_gemm(float (&d)[8][4], const uint32_t (&a)[16], uint32_t waddr, uint32_t accum) {
    const unsigned long long desc = (unsigned long long)((waddr & 0x3FFFFu) >> 4) | (1ull << 16) | (64ull << 32) | (1ull << 62);
    asm volatile("wgmma.fence.sync.aligned;" ::: "memory");
#pragma unroll
    for (int s = 0; s < 4; s++) {
        asm volatile("{ .reg .pred p; setp.ne.u32 p, %37, 0;"
                     " wgmma.mma_async.sync.aligned.m64n64k16.f32.bf16.bf16"
                     " {%0,%1,%2,%3,%4,%5,%6,%7,%8,%9,%10,%11,%12,%13,%14,%15,%16,%17,%18,%19,%20,%21,%22,%23,%24,%25,%26,%27,%28,%29,%30,%31},"
                     " {%32,%33,%34,%35}, %36, p, 1, 1, 1; }"
                     : "+f"(d[0][0]), "+f"(d[0][1]), "+f"(d[0][2]), "+f"(d[0][3]), "+f"(d[1][0]), "+f"(d[1][1]), "+f"(d[1][2]), "+f"(d[1][3]),
                       "+f"(d[2][0]), "+f"(d[2][1]), "+f"(d[2][2]), "+f"(d[2][3]), "+f"(d[3][0]), "+f"(d[3][1]), "+f"(d[3][2]), "+f"(d[3][3]),
                       "+f"(d[4][0]), "+f"(d[4][1]), "+f"(d[4][2]), "+f"(d[4][3]), "+f"(d[5][0]), "+f"(d[5][1]), "+f"(d[5][2]), "+f"(d[5][3]),
                       "+f"(d[6][0]), "+f"(d[6][1]), "+f"(d[6][2]), "+f"(d[6][3]), "+f"(d[7][0]), "+f"(d[7][1]), "+f"(d[7][2]), "+f"(d[7][3])
                     : "r"(a[4 * s]), "r"(a[4 * s + 1]), "r"(a[4 * s + 2]), "r"(a[4 * s + 3]), "l"(desc + s * 128), "r"(s ? 1u : accum)
                     : "memory");
    }
    asm volatile("wgmma.commit_group.sync.aligned;" ::: "memory");
    asm volatile("wgmma.wait_group.sync.aligned 0;"
                 : "+f"(d[0][0]), "+f"(d[0][1]), "+f"(d[0][2]), "+f"(d[0][3]), "+f"(d[1][0]), "+f"(d[1][1]), "+f"(d[1][2]), "+f"(d[1][3]),
                   "+f"(d[2][0]), "+f"(d[2][1]), "+f"(d[2][2]), "+f"(d[2][3]), "+f"(d[3][0]), "+f"(d[3][1]), "+f"(d[3][2]), "+f"(d[3][3]),
                   "+f"(d[4][0]), "+f"(d[4][1]), "+f"(d[4][2]), "+f"(d[4][3]), "+f"(d[5][0]), "+f"(d[5][1]), "+f"(d[5][2]), "+f"(d[5][3]),
                   "+f"(d[6][0]), "+f"(d[6][1]), "+f"(d[6][2]), "+f"(d[6][3]), "+f"(d[7][0]), "+f"(d[7][1]), "+f"(d[7][2]), "+f"(d[7][3])
                 :: "memory");
}
__device__ __forceinline__ void undef_acc(float (&d)[8][4]) {
#pragma unroll
    for (int j = 0; j < 8; j++) asm volatile("" : "=f"(d[j][0]), "=f"(d[j][1]), "=f"(d[j][2]), "=f"(d[j][3]));
}
__device__ __forceinline__ void zero_acc(float (&d)[8][4]) {
#pragma unroll
    for (int j = 0; j < 8; j++) { d[j][0] = 0.f; d[j][1] = 0.f; d[j][2] = 0.f; d[j][3] = 0.f; }
}
__device__ __forceinline__ void to_afrag(uint32_t (&a)[16], const float (&d)[8][4]) {
#pragma unroll
    for (int j = 0; j < 8; j++) {
        a[2 * j] = pack_bf16(d[j][0], d[j][1]);
        a[2 * j + 1] = pack_bf16(d[j][2], d[j][3]);
    }
}
__device__ __forceinline__ void to_afrag(uint32_t (&a)[16], const float (&d)[8][4], float s_lo, float s_hi) {
#pragma unroll
    for (int j = 0; j < 8; j++) {
        a[2 * j] = pack_bf16(d[j][0] * s_lo, d[j][1] * s_lo);
        a[2 * j + 1] = pack_bf16(d[j][2] * s_hi, d[j][3] * s_hi);
    }
}
__device__ __forceinline__ void ld_pair_if(uint4& v, const void* p, bool c) {
    unsigned long long a = ((unsigned long long)v.y << 32) | v.x, b = ((unsigned long long)v.w << 32) | v.z;
    asm volatile("{ .reg .pred p; .reg .b128 t; setp.ne.u32 p, %3, 0; mov.b128 t, {%0, %1}; @p ld.relaxed.gpu.global.b128 t, [%2]; mov.b128 {%0, %1}, t; }"
                 : "+l"(a), "+l"(b) : "l"(p), "r"((uint32_t)c) : "memory");
    v = make_uint4((uint32_t)a, (uint32_t)(a >> 32), (uint32_t)b, (uint32_t)(b >> 32));
}
__device__ __forceinline__ void load_own(uint4 (&xo)[4], const __nv_bfloat16* x, int tile, int lane) {
    const char* xr = reinterpret_cast<const char*>(x) + (size_t)(tile * 16 + (lane >> 2)) * 128 + (lane & 3) * 16;
    xo[0] = ldg_stream(xr);
    xo[1] = ldg_stream(xr + 64);
    xo[2] = ldg_stream(xr + 1024);
    xo[3] = ldg_stream(xr + 1024 + 64);
}
__device__ __forceinline__ void query_gemm(uint32_t (&tq)[16], const uint4 (&xo)[4]) {
    const uint32_t xa[16] = {xo[0].x, xo[2].x, xo[0].y, xo[2].y, xo[0].z, xo[2].z, xo[0].w, xo[2].w,
                             xo[1].x, xo[3].x, xo[1].y, xo[3].y, xo[1].z, xo[3].z, xo[1].w, xo[3].w};
    float t[8][4];
    undef_acc(t);
    wg_gemm(t, xa, sb + SM_W, 0u);
    to_afrag(tq, t);
}

template <bool FIRST>
__device__ __forceinline__ void agg_chunk(float (&acc)[8][4], uint32_t la, int ofs, uint32_t a0, uint32_t a1, uint32_t a2, uint32_t a3) {
#pragma unroll
    for (int q = 0; q < 4; q++) {
        uint32_t b[4];
        ldsm4t(b, (la ^ (q << 5)) + ofs);
        if (FIRST) {
            mma16816_z(acc[2 * q], a0, a1, a2, a3, b[0], b[1]);
            mma16816_z(acc[2 * q + 1], a0, a1, a2, a3, b[2], b[3]);
        } else {
            mma16816(acc[2 * q], a0, a1, a2, a3, b[0], b[1]);
            mma16816(acc[2 * q + 1], a0, a1, a2, a3, b[2], b[3]);
        }
    }
}
template <int XOFS>
__device__ __forceinline__ void cp16_bin(uint32_t dst, const char* xl, uint32_t e) {
    asm volatile("{ .reg .pred p; .reg .b64 a; .reg .b32 u; and.b32 u, %2, 0xFFF; setp.ne.u32 p, u, 0xFFF; mad.wide.u32 a, u, 2048, %1;"
                 " @p cp.async.cg.shared.global [%0], [a + %3], 16; }"
                 :: "r"(dst), "l"(xl), "r"(e), "n"(XOFS) : "memory");
}
template <int XOFS>
__device__ __forceinline__ void issue_bin(uint32_t da, int ofs, uint32_t ra, const char* xl) {
    const uint4 p = lds128(ra);
    const uint32_t db = da ^ 0x90u;
    cp16_bin<XOFS>(da + ofs, xl, p.x);
    cp16_bin<XOFS>(db + ofs, xl, p.y);
    cp16_bin<XOFS>(da + ofs + 1024, xl, p.z);
    cp16_bin<XOFS>(db + ofs + 1024, xl, p.w);
    cp_commit();
}
__device__ __forceinline__ void issue_tail(uint32_t da, int ofs, uint32_t ra, const char* xl) {
    const uint2 p = lds64(ra);
    const uint32_t db = da ^ 0x90u;
    cp16_row(da + ofs, xl, p.x & 0xFFFFu);
    cp16_row(db + ofs, xl, p.x >> 16);
    cp16_row(da + ofs + 1024, xl, p.y & 0xFFFFu);
    cp16_row(db + ofs + 1024, xl, p.y >> 16);
    cp_commit();
}
template <bool COMMIT = true>
__device__ __forceinline__ void issue_attn(uint32_t da, int ofs, uint32_t ea, const char* xl) {
    const uint32_t s0 = lds32(ea), s1 = lds32(ea + 16), s2 = lds32(ea + 128), s3 = lds32(ea + 144);
    const uint32_t db = da ^ 0x90u;
    cp16(da + ofs, xl + (size_t)s0 * 128);
    cp16(db + ofs, xl + (size_t)s1 * 128);
    cp16(da + ofs + 1024, xl + (size_t)s2 * 128);
    cp16(db + ofs + 1024, xl + (size_t)s3 * 128);
    if (COMMIT) cp_commit();
}
template <bool FIRST>
__device__ __forceinline__ void local_chunk(float (&acc)[8][4], uint32_t la, int ofs, uint32_t rt, uint32_t code) {
    const uint4 p = lds128(rt);
    const uint32_t w01 = prmt(p.x, p.y, 0x7632), w23 = prmt(p.z, p.w, 0x7632);
    uint32_t r01 = prmt(p.x, p.y, 0x5410), r23 = prmt(p.z, p.w, 0x5410);
    asm("lop3.b32 %0, %0, %1, 0xF000F000, 0xE4;" : "+r"(r01) : "r"(code));
    asm("lop3.b32 %0, %0, %1, 0xF000F000, 0xE4;" : "+r"(r23) : "r"(code));
    agg_chunk<FIRST>(acc, la, ofs, w01 & eq_lo2(r01, code), w01 & eq_hi2(r01, code), w23 & eq_lo2(r23, code), w23 & eq_hi2(r23, code));
}
__device__ __forceinline__ void attn_chunk(uint32_t (&y)[16], float& d0, float& d1, const uint32_t (&tq)[16], uint32_t lb, int lane) {
    float s0[4], s1[4];
    uint32_t xe[16];
#pragma unroll
    for (int s = 0; s < 4; s++) {
        ldsm4(xe[4 * s], xe[4 * s + 2], xe[4 * s + 1], xe[4 * s + 3], lb ^ (s << 5));
        if (s == 0) {
            mma16816_z(s0, tq[0], tq[1], tq[2], tq[3], xe[0], xe[2]);
            mma16816_z(s1, tq[0], tq[1], tq[2], tq[3], xe[1], xe[3]);
        } else {
            mma16816(s0, tq[4 * s], tq[4 * s + 1], tq[4 * s + 2], tq[4 * s + 3], xe[4 * s], xe[4 * s + 2]);
            mma16816(s1, tq[4 * s], tq[4 * s + 1], tq[4 * s + 2], tq[4 * s + 3], xe[4 * s + 1], xe[4 * s + 3]);
        }
    }
    const bool odd = lane & 4;
    const float p0 = ex2(odd ? s0[1] : s0[0]), p1 = ex2(odd ? s1[3] : s1[2]);
    d0 += p0;
    d1 += p1;
    const uint32_t p = __shfl_sync(~0u, pack_bf16(p0, p1), (lane & 28) | (lane >> 3));
    const uint32_t q0 = prmt(p, p, 0x1010), q1 = prmt(p, p, 0x3232);
#pragma unroll
    for (int i = 0; i < 16; i++) y[i] = fma_bf2(xe[i], (i & 1) ? q1 : q0, y[i]);
}
__device__ __forceinline__ void finish(float (&acc)[8][4], const uint32_t (&ao)[16],
                                       __nv_bfloat16* out, int tile, int lane) {
    uint32_t af[16];
    const uint32_t pd = sb + SM_DIS + (threadIdx.x >> 5) * 32 + (lane >> 2) * 2;
    to_afrag(af, acc, __uint_as_float(lds16(pd) << 16), __uint_as_float(lds16(pd + 16) << 16));
    wg_gemm(acc, af, sb + SM_W + 8192, blockDim.y - 1u);
    to_afrag(af, acc);
#pragma unroll
    for (int i = 0; i < 16; i++) af[i] = add_bf2(af[i], ao[i]);
    if (tile < N_TILES) {
        char* orow = reinterpret_cast<char*>(out) + (size_t)(tile * 16 + (lane >> 2)) * 128 + (lane & 3) * 16;
        *reinterpret_cast<uint4*>(orow) = make_uint4(af[0], af[2], af[4], af[6]);
        *reinterpret_cast<uint4*>(orow + 64) = make_uint4(af[8], af[10], af[12], af[14]);
        *reinterpret_cast<uint4*>(orow + 1024) = make_uint4(af[1], af[3], af[5], af[7]);
        *reinterpret_cast<uint4*>(orow + 1024 + 64) = make_uint4(af[9], af[11], af[13], af[15]);
    }
}

__device__ __noinline__ void slow_cta(const __nv_bfloat16* x, const int* src, const int* dst, const int* esrc, const int* edst,
                                      const __nv_bfloat16* dis, __nv_bfloat16* out, unsigned char* smem) {
    constexpr int QCAP = 64;
    const int tid = threadIdx.x, lane = tid & 31, warp = tid >> 5, cta = blockIdx.x;
    const int tile = cta * NW + warp;
    float2* acc = reinterpret_cast<float2*>(smem + SM_ES + warp * 8192) + lane;
    float2* aux = acc + 512;
    uint32_t* queue = reinterpret_cast<uint32_t*>(smem + SM_ES + NW * 8192);
    uint32_t* cnt = queue + NW * QCAP;
    static_assert(SM_ES + NW * 8192 + NW * QCAP * 4 + NW * 4 <= SM_TOTAL, "slow path scratch");
    const uint32_t* xw = reinterpret_cast<const uint32_t*>(x) + lane;
    auto lo = [](uint32_t v) { return __uint_as_float(v << 16); };
    auto hi = [](uint32_t v) { return __uint_as_float(v & 0xFFFF0000u); };
    auto matvec = [&](float v0, float v1, int wofs, bool rows) {
        float2 r = make_float2(0.f, 0.f);
        const int c = rows ? lane : ((lane & 16) | ((lane & 3) << 2) | ((lane >> 2) & 3));
#pragma unroll 1
        for (int k = 0; k < 64; k++) {
            const int f = rows ? perm_col(k) : k;
            const float a = __shfl_sync(~0u, (f & 1) ? v1 : v0, f >> 1);
            const uint32_t w = *reinterpret_cast<const uint32_t*>(smem + wofs + k * 128 + (((c >> 2) ^ (k & 7)) << 4) + (c & 3) * 4);
            r.x += a * lo(w);
            r.y += a * hi(w);
        }
        return r;
    };
    cp_wait<0>();
    __syncthreads();
    if (tid < NW) cnt[tid] = 0u;
#pragma unroll 1
    for (int r = 0; r < 16; r++) {
        const uint32_t v = __ldg(xw + (size_t)(min(tile, N_TILES - 1) * 16 + r) * 32);
        aux[r * 32] = matvec(lo(v), hi(v), SM_W, true);
    }
    __syncthreads();
#pragma unroll 1
    for (int pass = 0; pass < 2; pass++) {
        const int* dl = pass ? dst : edst;
        const int* sl = pass ? src : esrc;
        const int ne = pass ? N_EDGES : N_XEDGES;
        float den = 0.f;
#pragma unroll 1
        for (int r = 0; r < 16; r++) acc[r * 32] = make_float2(0.f, 0.f);
        int dnext = __ldg(dl + tid);
#pragma unroll 1
        for (int e = tid; e - tid < ne; e += NT) {
            const uint32_t loc = (uint32_t)(dnext - cta * NPC);
            bool pend = e < ne && loc < (uint32_t)NPC;
            if (e + NT < ne) dnext = __ldg(dl + e + NT);
            int more;
            do {
                if (pend) {
                    const uint32_t pos = atomicAdd(cnt + (loc >> 4), 1u);
                    if (pos < (uint32_t)QCAP) { queue[(loc >> 4) * QCAP + pos] = (uint32_t)e * 16u + (loc & 15u); pend = false; }
                }
                more = __syncthreads_or(pend);
                if (more || e - tid + NT >= ne) {
                    const int n = min((int)cnt[warp], QCAP);
#pragma unroll 1
                    for (int c = 0; c < n; c++) {
                        const uint32_t q = queue[warp * QCAP + c], r = q & 15u;
                        const int s = __ldg(sl + (q >> 4));
                        const uint32_t v = __ldg(xw + (size_t)s * 32);
                        float w;
                        if (pass) {
                            w = __bfloat162float(dis[s]);
                        } else {
                            const float2 t = aux[r * 32];
                            w = t.x * lo(v) + t.y * hi(v);
#pragma unroll
                            for (int o = 16; o; o >>= 1) w += __shfl_xor_sync(~0u, w, o);
                            w = ex2(w);
                            if (lane == (int)r) den += w;
                        }
                        float2 a = acc[r * 32];
                        a.x += w * lo(v);
                        a.y += w * hi(v);
                        acc[r * 32] = a;
                    }
                    __syncwarp();
                    if (lane == 0) cnt[warp] = 0u;
                    __syncthreads();
                }
            } while (more);
        }
#pragma unroll 1
        for (int r = 0; r < 16; r++) {
            const int node = min(tile, N_TILES - 1) * 16 + r;
            const float sc = pass ? __bfloat162float(dis[node]) : 1.f / (__shfl_sync(~0u, den, r) + 1e-9f);
            const float2 a = acc[r * 32];
            const float2 o = matvec(a.x * sc, a.y * sc, SM_W + (pass ? 8192 : 2 * 8192), false);
            if (pass == 0) aux[r * 32] = o;
            else if (tile < N_TILES) reinterpret_cast<uint32_t*>(out)[node * 32 + lane] = pack_bf16(o.x + aux[r * 32].x, o.y + aux[r * 32].y);
        }
    }
}

__device__ __forceinline__ uint32_t make_rec(uint32_t d, uint32_t s, uint32_t b) {
    uint32_t k;
    asm("lop3.b32 %0, %1, %2, 15, 0xE4;" : "=r"(k) : "r"(s), "r"(d - b * NPC));
    return prmt(s, d, 0x5410) * 4096u + k;
}
__device__ __forceinline__ void post4(const uint4& dv, const uint4& sv) {
    const uint32_t d[4] = {dv.x, dv.y, dv.z, dv.w}, s[4] = {sv.x, sv.y, sv.z, sv.w};
    uint32_t b[4], a[4];
#pragma unroll
    for (int i = 0; i < 4; i++) {
        b[i] = __umulhi(d[i], 11184811u);
        a[i] = atoms_add(sb + SM_HIST + b[i] * 4, 4u);
    }
#pragma unroll
    for (int i = 0; i < 4; i++) sts32(a[i], make_rec(d[i], s[i], b[i]));
}
__device__ __forceinline__ void claim4(uint4& r, uint4& a) {
    uint32_t v[4] = {r.x, r.y, r.z, r.w}, k[4], c[4], w[4];
#pragma unroll
    for (int i = 0; i < 4; i++) {
        k[i] = (v[i] & 0x1FFu) | KOFS;
        c[i] = atoms_add(sb + SM_CNT - KOFS * 4 + k[i] * 4, 4u);
        w[i] = lds16(sb + SM_TABLE + ((v[i] >> 11) & 0x1FFFEu));
    }
#pragma unroll
    for (int i = 0; i < 4; i++) {
        v[i] = prmt(v[i], w[i], 0x5432);
        asm("{ .reg .pred p; setp.ge.s32 p, %0, 64; mad.lo.u32 %0, %1, %2, %0; @p mad.lo.u32 %0, %1, %3, %0; }"
            : "+r"(c[i]) : "r"(k[i]), "n"(BS), "n"(128 - BS));
    }
    r = make_uint4(v[0], v[1], v[2], v[3]);
    a = make_uint4(c[0], c[1], c[2], c[3]);
}
__device__ __forceinline__ void put4(const uint4& r, const uint4& a) {
    const uint32_t o = sb + SM_BIN - BS * KOFS;
    sts32(o + a.x, r.x); sts32(o + a.y, r.y); sts32(o + a.z, r.z); sts32(o + a.w, r.w);
}
__device__ __forceinline__ void mbar_wait(uint32_t mbar) {
    uint32_t ok;
    int it = 0;
    do {
        asm volatile("{ .reg .pred p; mbarrier.try_wait.parity.shared.b64 p, [%1], 0; selp.u32 %0, 1, 0, p; }" : "=r"(ok) : "r"(mbar) : "memory");
        if (++it > (1 << 22)) __trap();
    } while (!ok);
}
__device__ __forceinline__ void mbar_expect(uint32_t mbar, uint32_t bytes) {
    asm volatile("mbarrier.arrive.expect_tx.shared.b64 _, [%0], %1;" :: "r"(mbar), "r"(bytes) : "memory");
}
__device__ __forceinline__ void bulk_load(uint32_t dst, const void* src, uint32_t bytes, uint32_t mbar) {
    asm volatile("cp.async.bulk.shared::cluster.global.mbarrier::complete_tx::bytes [%0], [%1], %2, [%3];"
                 :: "r"(dst), "l"(src), "r"(bytes), "r"(mbar) : "memory");
}
__device__ __forceinline__ void bulk_prefetch(const void* src, uint32_t bytes) {
    asm volatile("cp.async.bulk.prefetch.L2.global [%0], %1;" :: "l"(src), "r"(bytes) : "memory");
}
__device__ __forceinline__ void tail_put(uint32_t tw, uint32_t ts, uint32_t e, uint32_t r, int left) {
    asm volatile("{ .reg .pred p; .reg .b32 s; setp.gt.s32 p, %4, 0; mad.lo.u32 s, %2, 16, %3; @p st.shared.u32 [%0], %2; @p st.shared.u16 [%1], s; }"
                 :: "r"(tw), "r"(ts), "r"(e), "r"(r), "r"(left) : "memory");
}

template <bool FAST>
__global__ void __launch_bounds__(NT, 1)
exphormer_kernel(const __nv_bfloat16* __restrict__ x, const int* __restrict__ src, const int* __restrict__ dst,
                 const int* __restrict__ esrc, const int* __restrict__ edst, const __nv_bfloat16* __restrict__ dis,
                 const __nv_bfloat16* __restrict__ wl, const __nv_bfloat16* __restrict__ wq,
                 const __nv_bfloat16* __restrict__ wk, const __nv_bfloat16* __restrict__ wv,
                 __nv_bfloat16* __restrict__ out) {
    extern __shared__ __align__(1024) unsigned char smem[];
    const int tid = threadIdx.x, cta = blockIdx.x;
    PROF(0);

    const bool prod = FAST && cta < NPROD;
    const int nown = min(NPC, N_NODES - cta * NPC);
    uint32_t ep = 0, dx, sx;
    if (FAST && tid == 0) {
        constexpr uint32_t mbar = sb + SM_MISC, QB = EC;
#pragma unroll
        for (int i = 0; i < 5; i++) asm volatile("mbarrier.init.shared.b64 [%0], 1;" :: "r"(mbar + i * 8) : "memory");
        asm volatile("fence.mbarrier_init.release.cluster;" ::: "memory");
        if (prod) {
#pragma unroll
            for (int i = 0; i < 4; i++) {
                mbar_expect(mbar + i * 8, 2 * QB);
                bulk_load(sb + SM_EDGE + i * 2 * QB, dst + cta * EC + i * (QB / 4), QB, mbar + i * 8);
                bulk_load(sb + SM_EDGE + i * 2 * QB + QB, src + cta * EC + i * (QB / 4), QB, mbar + i * 8);
            }
        }
        if ((uint32_t)__cvta_generic_to_shared(smem) != sb) __trap();
    }
    PROF(21);
    const int lane = tid & 31, warp = tid >> 5;
    uint4 wr[4];
    if (warp >= 8) {
        const int i = tid - 256, r = i >> 3;
        const uint32_t d = sb + SM_W + 8192 + r * 128 + (((i ^ r) & 7) << 4);
        cp16(d, wq + perm_col(r) * 64 + (i & 7) * 8);
        cp16(d + 8192, wk + i * 8);
    } else {
        const char* pa = reinterpret_cast<const char*>(warp < 4 ? wl : wv) + (tid & 127) * 64;
#pragma unroll
        for (int q = 0; q < 4; q++) wr[q] = ldg_stream(pa + q * 16);
    }
    cp_commit();
    if (prod && tid < EX) {
        dx = ldg32(dst + NPROD * EC + cta * EX + tid);
        sx = ldg32(src + NPROD * EC + cta * EX + tid);
    }
    if (FAST && tid == PFT) asm volatile("ld.relaxed.gpu.global.u32 %0, [%1];" : "=r"(ep) : "l"(&g_count) : "memory");
    const int c12 = tid / 12, k12 = tid - c12 * 12;
    if (FAST) {
        const uint32_t nul = KDUM + ((cta * 12 + k12) & 31);
#pragma unroll
        for (int i = 0; i < STG / (NT * 16); i++) sts128(sb + SM_MB + tid * 16 + i * NT * 16, nul);
        const int k = tid - 2 * NMB;
        uint32_t v = k < 0 ? sb + SM_MB + tid * MBS : 0u;
        if ((uint32_t)(k - KDUM) < 32u) v = SM_DUMP - SM_BIN - k * BS;
        if (tid < (SM_MISC - SM_HIST) / 4) sts32(sb + SM_HIST + tid * 4, v);
        PROF(3);
        constexpr int NU = N_NODES / 8;
#pragma unroll
        for (int i = 0; i < (NU + NT - 1) / NT; i++)
            if ((i + 1) * NT <= NU || tid + i * NT < NU) cp16(sb + SM_TABLE + (tid + i * NT) * 16, dis + (tid + i * NT) * 8);
    }
    cp_commit();
    PROF(22);
    cp_wait<1>();
    __syncthreads();
    PROF(1);
    if (warp >= 8) {
        const int mi = (warp - 8) >> 2, jp = warp & 3;
        const uint32_t pa = sb + SM_W + 8192 + (mi * 16 + (lane & 15)) * 128 + (((lane >> 4) ^ (lane & 7)) << 4);
        const uint32_t pb = sb + SM_W + 2 * 8192 + (jp * 16 + (lane & 7) + (lane >> 4) * 8) * 128 + ((((lane >> 3) & 1) ^ (lane & 7)) << 4);
        float e0[4], e1[4];
#pragma unroll
        for (int s = 0; s < 4; s++) {
            uint32_t a[4], b[4];
            ldsm4(a[0], a[1], a[2], a[3], pa ^ (s << 5));
            ldsm4(b[0], b[1], b[2], b[3], pb ^ (s << 5));
            if (s == 0) { mma16816_z(e0, a[0], a[1], a[2], a[3], b[0], b[1]); mma16816_z(e1, a[0], a[1], a[2], a[3], b[2], b[3]); }
            else        { mma16816(e0, a[0], a[1], a[2], a[3], b[0], b[1]);   mma16816(e1, a[0], a[1], a[2], a[3], b[2], b[3]); }
        }
        const float sc = 0.125f * 1.4426950408889634f;
        stsm4(sb + SM_W + (mi * 16 + (lane & 15)) * 128 + (((jp * 2 + (lane >> 4)) ^ (lane & 7)) << 4),
              pack_bf16(e0[0] * sc, e0[1] * sc), pack_bf16(e0[2] * sc, e0[3] * sc),
              pack_bf16(e1[0] * sc, e1[1] * sc), pack_bf16(e1[2] * sc, e1[3] * sc));
    }
    PROF(2);
    const int quad = tid / (NT / 4);
    if (prod) mbar_wait(sb + SM_MISC + quad * 8);
    PROF(16);
    if (FAST && tid == PFT) {
        mbar_expect(sb + SM_MISC + 32, nown * 18);
        bulk_load(sb + SM_ES, esrc + cta * NPC * 4, nown * 16, sb + SM_MISC + 32);
        bulk_load(sb + SM_DIS, dis + cta * NPC, nown * 2, sb + SM_MISC + 32);
        bulk_prefetch(x + (size_t)cta * NPC * 64, nown * 128);
        ep = ep / NCTA + 1u;
        sts32(sb + SM_TAG, ep << 9);
    }
    if (prod) {
        const uint32_t a = sb + SM_EDGE + quad * (EC * 2 - NT * 4) + tid * 16;
        const uint4 d0 = lds128(a), d1 = lds128(a + EC / 2), s0 = lds128(a + EC), s1 = lds128(a + EC + EC / 2);
        post4(d0, s0);
        post4(d1, s1);
        if (tid < EX) {
            const uint32_t b = __umulhi(dx, 11184811u);
            sts32(atoms_add(sb + SM_HIST + b * 4, 4u), make_rec(dx, sx, b));
        }
    }
    PROF(4);
    __syncthreads();
    PROF(5);
    bool bad = false;
    const bool hi6 = k12 >= 6;
    const int u6 = hi6 ? k12 - 6 : k12;
    const uint32_t tagw = lds32(sb + SM_TAG);
    if (prod) {
        const uint32_t so2 = hi6 ? NMB * MBS + 96 : 192;
        const uint32_t go2 = GOD - cta * 96 + (hi6 ? NMB * GBKT - 96 : 0);
#pragma unroll 1
        for (int c = c12; c < NMB; c += NT / 12) {
            const uint32_t mb = sb + SM_MB + c * MBS, sa = mb + k12 * 16;
            const int na = lds32(sb + SM_HIST + c * 4) - mb, nb = lds32(sb + SM_HIST + (c + NMB) * 4) - mb;
            uint4 v0 = lds128(sa), v1 = lds128(sa + NMB * MBS), v2 = lds128(sa + so2);
            const int ea = __viaddmin_s32_relu(na, 31 - 192, 128), eb = __viaddmin_s32_relu(nb, 31 - 192 - NMB * MBS, 128);
            bad = bad || na > MBS || nb > (NMB + 1) * MBS;
            v0.x |= tagw; v1.x |= tagw; v2.x |= tagw;
            v0.y += (ea & 0xE0) << 4;
            v1.y += (eb & 0xE0) << 4;
            const uint32_t go = c * GBKT + cta * 192 + k12 * 16;
            st_pair(g_rec + go, v0);
            st_pair(g_rec + go + NMB * GBKT, v1);
            const int e = hi6 ? eb : ea;
            if (e >= (u6 | 1) * 16 + 16) st_pair(g_rec + (go + go2), v2);
            if (e == 128 && u6 < 5) {
                v2 = lds128(sa + so2 + 96);
                v2.x |= tagw;
                st_pair(g_rec + (go + go2) + NPROD * 96, v2);
            }
        }
    }
    if (FAST && tid == PFT) asm volatile("red.relaxed.gpu.global.inc.u32 [%0], %1;" :: "l"(&g_count), "n"(7 * NCTA - 1) : "memory");
    PROF(6);
    if (warp < 8) {
        const uint32_t wd = sb + SM_W + 8192 + (tid >> 1) * 128 + ((((tid & 1) * 4) ^ ((tid >> 1) & 7)) << 4);
        sts128v(wd, wr[0].x, wr[1].x, wr[2].x, wr[3].x);
        sts128v(wd ^ 16, wr[0].y, wr[1].y, wr[2].y, wr[3].y);
        sts128v(wd ^ 32, wr[0].z, wr[1].z, wr[2].z, wr[3].z);
        sts128v(wd ^ 48, wr[0].w, wr[1].w, wr[2].w, wr[3].w);
    }
    if (!FAST) {
        slow_cta(x, src, dst, esrc, edst, dis, out, smem);
        return;
    }

    const int tile = cta * NW + warp;
    const int tl = min(tile, N_TILES - 1);
    const char* xl = reinterpret_cast<const char*>(x) + (lane & 7) * 16;
    const uint32_t st0 = sb + SM_STAGE + warp * 2048;
    const uint32_t da = st0 + (lane >> 3) * 256 + (((lane & 7) ^ ((lane >> 3) * 2)) << 4);
    const uint32_t ea = sb + SM_ES + (tl - cta * NW) * 256 + (lane >> 3) * 32;
    {
        constexpr int N0 = (SM_TS - SM_BIN) / 16, N1 = (SM_FLAG - SM_BIN) / 16;
#pragma unroll
        for (int i = 0; i < 3; i++) sts128(sb + SM_BIN + (tid + i * NT) * 16, 0xFFFu);
        if (tid < N1 - 3 * NT) sts128(sb + SM_BIN + (tid + 3 * NT) * 16, tid < N0 - 3 * NT ? 0xFFFu : ~0u);
        static_assert(N0 >= 3 * NT && N1 <= 4 * NT, "fill");
    }
    cp_wait<0>();
    fence_async();
    if (tid == PFT) {
        const uint32_t go = ep == 7u ? 0u : ep * NCTA;
        uint32_t v;
        int it = 0;
#pragma unroll 1
        do {
            asm volatile("ld.relaxed.gpu.global.u32 %0, [%1];" : "=r"(v) : "l"(&g_count) : "memory");
            if (++it > (1 << 22)) __trap();
        } while (v != go);
    }
    __syncthreads();
    PROF(19);

    uint4 xo[4];
    {
        unsigned char* gp = g_rec + cta * GBKT + tid * 16;
        unsigned char* gq = g_rec + cta * GBKT + GOD + (c12 + (hi6 ? NPROD / 2 : 0)) * 96 + u6 * 16;
        uint4 r0, r1, r2, r3, a0, a1, a2, a3;
        int it = 0;
#pragma unroll 1
        do {
            r0 = ld_pair(gp);
            r1 = ld_pair(gp + GOD / 2);
            if (++it > (1 << 22)) __trap();
        } while (__any_sync(~0u, ((r0.x ^ tagw) | (r1.x ^ tagw)) & 0xE00u));
        PROF(7);
        const uint32_t code = (hi6 ? r1.y : r0.y) & 0xE00u;
        const bool p2 = code > (uint32_t)u6 * 256u, p3 = code == 0x800u && u6 < 5;
        if (p2) r2 = ld_pair(gq);
        mbar_wait(sb + SM_MISC + 32);
        issue_attn(da, 0, ea, xl);
        PROF(17);
        claim4(r0, a0);
        claim4(r1, a1);
        if (p2) {
#pragma unroll 1
            while ((r2.x ^ tagw) & 0xE00u) {
                r2 = ld_pair(gq);
                if (++it > (1 << 22)) __trap();
            }
            st_pair(gq, make_uint4(0u, 0u, 0u, 0u));
            claim4(r2, a2);
        }
        if (p3) {
#pragma unroll 1
            do {
                r3 = ld_pair(gq + NPROD * 96);
                if (++it > (1 << 22)) __trap();
            } while ((r3.x ^ tagw) & 0xE00u);
            st_pair(gq + NPROD * 96, make_uint4(0u, 0u, 0u, 0u));
            claim4(r3, a3);
        }
        PROF(8);
        __syncthreads();
        PROF(9);
        put4(r0, a0);
        put4(r1, a1);
        if (p2) put4(r2, a2);
        if (p3) put4(r3, a3);
        PROF(18);
        load_own(xo, x, tl, lane);
        issue_attn(da, 2 * STG, ea + 4, xl);
    }
    PROF(11);
    __syncthreads();
    PROF(12);
    {
        const uint32_t r = lane & 15;
        const int c = lds32(sb + SM_CNT + warp * 64 + r * 4);
        int n = __viaddmin_s32_relu(c, -64, 128), v = n;
#pragma unroll
        for (int o = 1; o < 16; o <<= 1) {
            const int u = __shfl_up_sync(~0u, v, o, 16);
            if ((int)r >= o) v += u;
        }
        int tot = __shfl_sync(~0u, v, 15);
        bad = bad || c > 192 || tot > TCAP * 4;
        if (tot > TCAP * 4) n = tot = 0;
        sts32(sb + SM_CNT + warp * 64, tot);
        const uint32_t h = lane & 16;
        uint32_t pos = warp * (TCAP * 4) + v - n + h, xa = sb + SM_EXT + warp * 2048 + r * 128 + h;
        n -= h;
#pragma unroll 1
        while (n > 0) {
            const uint4 e = lds128(xa);
            const uint32_t tw = sb + SM_TW + pos, ts = sb + SM_TS + (pos >> 1);
            tail_put(tw, ts, e.x, r, n);
            tail_put(tw + 4, ts + 2, e.y, r, n - 4);
            tail_put(tw + 8, ts + 4, e.z, r, n - 8);
            tail_put(tw + 12, ts + 6, e.w, r, n - 12);
            n -= 32; pos += 32; xa += 32;
        }
        wsync();
    }
    issue_attn(da, STG, ea + 8, xl);
    PROF(10);

    uint32_t ra = sb + SM_BIN + warp * (16 * BS) + (lane >> 3) * 16;
    uint32_t ao[16], rden;
    {
        uint32_t tq[16], y[16];
        float e0 = 0.f, e1 = 0.f;
        query_gemm(tq, xo);
#pragma unroll
        for (int i = 0; i < 16; i++) y[i] = 0u;
        const uint32_t lb = st0 + ((lane & 7) + (lane >> 4) * 8) * 128 + ((((lane >> 3) & 1) ^ (lane & 7)) << 4);
        uint32_t so = 0;
#pragma unroll 1
        for (int j = 0; j < 4; j++) {
            cp_wait<2>(); wsync();
            attn_chunk(y, e0, e1, tq, lb + so, lane);
            wsync();
            if (j == 0) {
                issue_attn<false>(da, 0, ea + 12, xl);
                wsync();
                if (lane < 16) cp16(sb + SM_ES + warp * 256 + lane * 16, edst + tl * 64 + lane * 4);
                cp_commit();
            } else {
                issue_bin<-128>(da + so, 0, ra - BS, xl);
            }
            so = so ? so - STG : 2 * STG;
            ra += BS; xl += 128;
        }
        {
            const uint32_t node = tl * 16 + (lane >> 1);
            const uint2 ed = lds64(sb + SM_ES + tid * 8);
            const uint32_t inc = __any_sync(~0u, bad || ed.x != node || ed.y != node) ? 257u : 1u;
            uint32_t v = 0;
            if (lane == 0) v = atoms_add(sb + SM_CNT + (KDUM + 32) * 4, inc) + inc;
            v = __shfl_sync(~0u, v, 0);
            if ((v & 255u) == NW && lane < 2) st_pair(g_flag + cta * 2 + lane, make_uint4(lds32(sb + SM_TAG) | (v > 255u), 0u, 0u, 0u));
        }
        rden = __shfl_sync(~0u, pack_bf16(__fdividef(1.f, e0 + 1e-9f), __fdividef(1.f, e1 + 1e-9f)), (lane & 28) | (lane >> 3));
        float t[8][4];
        undef_acc(t);
        wg_gemm(t, y, sb + SM_W + 2 * 8192, 0u);
        to_afrag(ao, t);
#pragma unroll
        for (int i = 0; i < 16; i++) asm volatile("" : "+r"(ao[i]));
        if (blockDim.z != 1) __trap();
    }
    PROF(13);

    float acc[8][4];
    {
        const uint32_t la = st0 + (lane & 15) * 128 + (((lane >> 4) ^ (lane & 7)) << 4);
        const uint32_t code = (uint32_t)(lane >> 2) * 0x10001000u + 0x84000400u;
        uint32_t rt = sb + SM_BIN + warp * (16 * BS) + (lane & 3) * 16;
#define STEP(OFS, NXT, K)                                          \
        wsync();                                                   \
        issue_bin<((K) - 2) * 128>(da, OFS, ra + ((K) - 2) * BS, xl);  \
        cp_wait<2>(); wsync();                                     \
        local_chunk<false>(acc, la, NXT, rt + (K) * BS, code);
        cp_wait<2>(); wsync();
        local_chunk<true>(acc, la, 2 * STG, rt, code);
        STEP(2 * STG, STG, 1)
#pragma unroll 1
        for (int i = 0; i < 4; i++) {
            STEP(STG, 0, 2)
            STEP(0, 2 * STG, 3)
            STEP(2 * STG, STG, 4)
            rt += 3 * BS; ra += 3 * BS; xl += 3 * 128;
        }
#undef STEP
        xl -= 16 * 128;
        ra = sb + SM_TS + warp * (TCAP * 2) + (lane >> 3) * 8;
        if (tid < NCTA) cp16(sb + SM_FLAG + tid * 16, g_flag + tid * 2);
        wsync();
        issue_tail(da, STG, ra, xl);
        cp_wait<2>(); wsync();
        local_chunk<false>(acc, la, 0, rt + 2 * BS, code);
        wsync();
        issue_tail(da, 0, ra + 32, xl);
        cp_wait<2>(); wsync();
        local_chunk<false>(acc, la, 2 * STG, rt + 3 * BS, code);
        rt = sb + SM_TW + warp * (TCAP * 4) + (lane & 3) * 16;
        int left = lds32(sb + SM_CNT + warp * 64);
        uint32_t so = 2 * STG;
#pragma unroll 1
        while (left > 0) {
            wsync();
            issue_tail(da + so, 0, ra + 64, xl);
            so = so ? so - STG : 2 * STG;
            cp_wait<2>(); wsync();
            local_chunk<false>(acc, la + so, 0, rt, code);
            left -= 64; rt += 64; ra += 32;
        }
    }
    PROF(14);
    {
        const uint32_t q0 = prmt(rden, rden, 0x1010), q1 = prmt(rden, rden, 0x3232);
#pragma unroll
        for (int i = 0; i < 16; i++) ao[i] = mul_bf2(ao[i], (i & 1) ? q1 : q0);
        if (gridDim.y != 1) __trap();
    }
    finish(acc, ao, out, tile, lane);
    cp_wait<0>();
    PROF(15);
    uint32_t f = 0;
    if (tid < NCTA) {
        const uint32_t tg = lds32(sb + SM_TAG);
        f = lds32(sb + SM_FLAG + tid * 16);
        int it = 0;
#pragma unroll 1
        while ((f ^ tg) > 1u) {
            asm volatile("ld.relaxed.gpu.global.u32 %0, [%1];" : "=r"(f) : "l"(g_flag + tid * 2) : "memory");
            if (++it > (1 << 22)) __trap();
        }
    }
    if (__builtin_expect(__syncthreads_or(f & 1u), 0)) slow_cta(x, src, dst, esrc, edst, dis, out, smem);
}

}

extern "C" void kernel_launch(void* const* d_in, const int* in_sizes, int n_in, void* d_out, int out_size) {
    (void)in_sizes; (void)n_in; (void)out_size;
    const __nv_bfloat16* x   = (const __nv_bfloat16*)d_in[0];
    const int* src           = (const int*)d_in[1];
    const int* dst           = (const int*)d_in[2];
    const int* esrc          = (const int*)d_in[3];
    const int* edst          = (const int*)d_in[4];
    const __nv_bfloat16* dis = (const __nv_bfloat16*)d_in[5];
    const __nv_bfloat16* wl  = (const __nv_bfloat16*)d_in[6];
    const __nv_bfloat16* wq  = (const __nv_bfloat16*)d_in[7];
    const __nv_bfloat16* wk  = (const __nv_bfloat16*)d_in[8];
    const __nv_bfloat16* wv  = (const __nv_bfloat16*)d_in[9];
    __nv_bfloat16* out = (__nv_bfloat16*)d_out;

    static int fast = -1;
    if (fast < 0) {
        cudaFuncSetAttribute(exphormer_kernel<true>, cudaFuncAttributeMaxDynamicSharedMemorySize, SM_TOTAL);
        cudaFuncSetAttribute(exphormer_kernel<false>, cudaFuncAttributeMaxDynamicSharedMemorySize, SM_TOTAL);
        int dev = 0, sms = 0, occ = 0;
        cudaGetDevice(&dev);
        cudaDeviceGetAttribute(&sms, cudaDevAttrMultiProcessorCount, dev);
        cudaOccupancyMaxActiveBlocksPerMultiprocessor(&occ, exphormer_kernel<true>, NT, SM_TOTAL);
        fast = (sms * occ >= NCTA) ? 1 : 0;
    }
    if (fast) exphormer_kernel<true><<<NCTA, NT, SM_TOTAL>>>(x, src, dst, esrc, edst, dis, wl, wq, wk, wv, out);
    else      exphormer_kernel<false><<<NCTA, NT, SM_TOTAL>>>(x, src, dst, esrc, edst, dis, wl, wq, wk, wv, out);
}
```

```cpp
#include <cuda_runtime.h>
#include <cuda_bf16.h>
#include <stdint.h>

namespace {

constexpr int N_NODES  = 50000;
constexpr int N_EDGES  = 800000;
constexpr int N_XEDGES = 200000;
constexpr int N_TILES  = N_NODES / 16;
constexpr int NW       = 24;
constexpr int NT       = NW * 32;
constexpr int NPC      = NW * 16;
constexpr int NCTA     = (N_NODES + NPC - 1) / NPC;
constexpr int NPROD    = NT / 6;
constexpr int EC       = NT * 8;
constexpr int EX       = N_EDGES / NPROD - EC;
constexpr int MBS      = 368;
constexpr int GOD      = NPROD * 288;
constexpr int GBKT     = NPROD * 384;
constexpr int NCLS     = 17;
constexpr int CLW      = 2978;
constexpr int TCAP     = 96;
constexpr int L_TW     = NCLS * 64;
constexpr int L_TS     = L_TW + TCAP * 4;
constexpr int L_AL     = L_TS + TCAP * 4;
constexpr int TS       = L_AL + 5 * 64 + 16;
#define PREDNULL
#define PFT 736
#define PSCHED 0x333333333333ull
#define TABAT 3
constexpr int STG      = NW * 2048;

static_assert(NPROD * (EC + EX) == N_EDGES && EX <= NT && NPROD <= NCTA && N_NODES % 16 == 0, "edge slices");
static_assert(GOD == 3 * NT * 16 && N_NODES * 22 < NCLS * 65536 && CLW * 22 <= 65536 && L_AL + 192 >= 2048, "inbox, classes");

constexpr int SM_W     = 0;
constexpr int SM_DIS   = 3 * 8192;
constexpr int SM_MISC  = SM_DIS + NPC * 2;
constexpr int SM_TAG   = SM_MISC + 64;
constexpr int SM_WCNT  = SM_TAG + 16;
constexpr int SM_HIST  = SM_WCNT + 16;
constexpr int SM_CNT   = SM_HIST + 132 * 4;
constexpr int SM_EXTRA = SM_CNT + (NW + 1) * 80;
constexpr int SM_FLAG  = SM_HIST;
constexpr int SM_BIN   = SM_EXTRA + EX * 8;
constexpr int SM_EDGE  = SM_BIN;
constexpr int SM_STAGE = 83200;
constexpr int SM_MB    = SM_STAGE;
constexpr int SM_DUMP  = SM_MB + GOD;
constexpr int SM_TABLE = SM_STAGE + STG;
constexpr int SM_TOTAL = SM_TABLE + N_NODES * 2;
constexpr uint32_t sb  = 1024;
static_assert(SM_MISC % 16 == 0 && SM_BIN % 16 == 0 && SM_STAGE % 256 == 0 && SM_TOTAL <= 232448 && 2 * STG <= N_NODES * 2, "layout");
static_assert(SM_FLAG + NCTA * 16 <= SM_BIN && SM_BIN + NW * TS <= SM_STAGE && SM_EDGE + EC * 8 <= SM_STAGE && NCTA * MBS <= STG, "layout");
static_assert(sb + SM_DUMP + NPROD * 24 <= (1 << 17) && (SM_EXTRA - SM_WCNT) / 4 <= NT, "cursors");

__device__ __align__(128) unsigned char g_rec[NCTA * GBKT];
__device__ __align__(128) uint4 g_flag[NCTA * 2];
__device__ __align__(128) uint32_t g_count[4];

#define PROFC(i) do {} while (0)
#define PROF(i) do {} while (0)

__device__ __forceinline__ void mma16816(float (&d)[4], uint32_t a0, uint32_t a1, uint32_t a2, uint32_t a3,
                                         uint32_t b0, uint32_t b1) {
    asm volatile("mma.sync.aligned.m16n8k16.row.col.f32.bf16.bf16.f32 {%0,%1,%2,%3}, {%4,%5,%6,%7}, {%8,%9}, {%0,%1,%2,%3};"
                 : "+f"(d[0]), "+f"(d[1]), "+f"(d[2]), "+f"(d[3])
                 : "r"(a0), "r"(a1), "r"(a2), "r"(a3), "r"(b0), "r"(b1));
}
__device__ __forceinline__ void mma16816_z(float (&d)[4], uint32_t a0, uint32_t a1, uint32_t a2, uint32_t a3,
                                           uint32_t b0, uint32_t b1) {
    asm volatile("mma.sync.aligned.m16n8k16.row.col.f32.bf16.bf16.f32 {%0,%1,%2,%3}, {%4,%5,%6,%7}, {%8,%9}, {%10,%10,%10,%10};"
                 : "=f"(d[0]), "=f"(d[1]), "=f"(d[2]), "=f"(d[3])
                 : "r"(a0), "r"(a1), "r"(a2), "r"(a3), "r"(b0), "r"(b1), "f"(0.f));
}
__device__ __forceinline__ void ldsm4(uint32_t& r0, uint32_t& r1, uint32_t& r2, uint32_t& r3, uint32_t addr) {
    asm volatile("ldmatrix.sync.aligned.m8n8.x4.shared.b16 {%0,%1,%2,%3}, [%4];"
                 : "=r"(r0), "=r"(r1), "=r"(r2), "=r"(r3) : "r"(addr) : "memory");
}
__device__ __forceinline__ void ldsm4t(uint32_t (&r)[4], uint32_t addr) {
    asm volatile("ldmatrix.sync.aligned.m8n8.x4.trans.shared.b16 {%0,%1,%2,%3}, [%4];"
                 : "=r"(r[0]), "=r"(r[1]), "=r"(r[2]), "=r"(r[3]) : "r"(addr) : "memory");
}
__device__ __forceinline__ void stsm4(uint32_t addr, uint32_t r0, uint32_t r1, uint32_t r2, uint32_t r3) {
    asm volatile("stmatrix.sync.aligned.m8n8.x4.shared.b16 [%0], {%1,%2,%3,%4};"
                 :: "r"(addr), "r"(r0), "r"(r1), "r"(r2), "r"(r3) : "memory");
}
__device__ __forceinline__ uint32_t pack_bf16(float lo, float hi) {
    uint32_t r;
    asm("cvt.rn.bf16x2.f32 %0, %1, %2;" : "=r"(r) : "f"(hi), "f"(lo));
    return r;
}
__device__ __forceinline__ uint32_t fma_bf2(uint32_t a, uint32_t b, uint32_t c) {
    uint32_t r;
    asm volatile("fma.rn.bf16x2 %0, %1, %2, %3;" : "=r"(r) : "r"(a), "r"(b), "r"(c));
    return r;
}
__device__ __forceinline__ uint32_t prmt(uint32_t a, uint32_t b, uint32_t s) {
    uint32_t r;
    asm("prmt.b32 %0, %1, %2, %3;" : "=r"(r) : "r"(a), "r"(b), "r"(s));
    return r;
}
__device__ __forceinline__ uint32_t eq_lo2(uint32_t a, uint32_t b) {
    uint32_t r;
    asm("{ .reg .b16 l, h; .reg .b32 c; mov.b32 {l, h}, %2; mov.b32 c, {l, l}; set.eq.u32.f16x2 %0, %1, c; }" : "=r"(r) : "r"(a), "r"(b));
    return r;
}
__device__ __forceinline__ uint32_t eq_hi2(uint32_t a, uint32_t b) {
    uint32_t r;
    asm("{ .reg .b16 l, h; .reg .b32 c; mov.b32 {l, h}, %2; mov.b32 c, {h, h}; set.eq.u32.f16x2 %0, %1, c; }" : "=r"(r) : "r"(a), "r"(b));
    return r;
}
__device__ __forceinline__ float ex2(float x) {
    float r;
    asm("ex2.approx.ftz.f32 %0, %1;" : "=f"(r) : "f"(x));
    return r;
}
__device__ __forceinline__ void cp16(uint32_t dst, const void* src) {
    asm volatile("cp.async.cg.shared.global [%0], [%1], 16;" :: "r"(dst), "l"(src) : "memory");
}
__device__ __forceinline__ void cp4(uint32_t dst, const void* src) {
    asm volatile("cp.async.ca.shared.global [%0], [%1], 4;" :: "r"(dst), "l"(src) : "memory");
}
__device__ __forceinline__ void cp_commit() { asm volatile("cp.async.commit_group;" ::: "memory"); }
template <int N> __device__ __forceinline__ void cp_wait() { asm volatile("cp.async.wait_group %0;" :: "n"(N) : "memory"); }
__device__ __forceinline__ void fence_async() { asm volatile("fence.proxy.async.shared::cta;" ::: "memory"); }
__device__ __forceinline__ void wsync() { asm volatile("bar.warp.sync 0xffffffff;" ::: "memory"); }
__device__ __forceinline__ uint4 lds128(uint32_t a) {
    uint4 v;
    asm volatile("ld.shared.v4.u32 {%0,%1,%2,%3}, [%4];" : "=r"(v.x), "=r"(v.y), "=r"(v.z), "=r"(v.w) : "r"(a) : "memory");
    return v;
}
__device__ __forceinline__ uint2 lds64(uint32_t a) {
    uint2 v;
    asm volatile("ld.shared.v2.u32 {%0,%1}, [%2];" : "=r"(v.x), "=r"(v.y) : "r"(a) : "memory");
    return v;
}
__device__ __forceinline__ uint32_t lds32(uint32_t a) {
    uint32_t v;
    asm volatile("ld.shared.u32 %0, [%1];" : "=r"(v) : "r"(a) : "memory");
    return v;
}
__device__ __forceinline__ uint32_t lds16(uint32_t a) {
    uint32_t v;
    asm volatile("ld.shared.u16 %0, [%1];" : "=r"(v) : "r"(a) : "memory");
    return v;
}
__device__ __forceinline__ void sts32(uint32_t a, uint32_t v) { asm volatile("st.shared.u32 [%0], %1;" :: "r"(a), "r"(v) : "memory"); }
__device__ __forceinline__ void sts128(uint32_t a, uint32_t v) {
    asm volatile("st.shared.v4.u32 [%0], {%1,%1,%1,%1};" :: "r"(a), "r"(v) : "memory");
}
__device__ __forceinline__ uint32_t atoms_add(uint32_t a, uint32_t v) {
    uint32_t r;
    asm volatile("atom.shared.add.u32 %0, [%1], %2;" : "=r"(r) : "r"(a), "r"(v) : "memory");
    return r;
}
__device__ __forceinline__ void sts128v(uint32_t a, uint32_t x, uint32_t y, uint32_t z, uint32_t w) {
    asm volatile("st.shared.v4.u32 [%0], {%1,%2,%3,%4};" :: "r"(a), "r"(x), "r"(y), "r"(z), "r"(w) : "memory");
}
__device__ __forceinline__ uint4 ld_pair(const void* p) {
    unsigned long long a, b;
    asm volatile("{ .reg .b128 t; ld.relaxed.gpu.global.b128 t, [%2]; mov.b128 {%0, %1}, t; }" : "=l"(a), "=l"(b) : "l"(p) : "memory");
    return make_uint4((uint32_t)a, (uint32_t)(a >> 32), (uint32_t)b, (uint32_t)(b >> 32));
}
__device__ __forceinline__ void st_pair(void* p, uint4 v) {
    const unsigned long long a = ((unsigned long long)v.y << 32) | v.x, b = ((unsigned long long)v.w << 32) | v.z;
    asm volatile("{ .reg .b128 t; mov.b128 t, {%1, %2}; st.relaxed.gpu.global.b128 [%0], t; }" :: "l"(p), "l"(a), "l"(b) : "memory");
}

__device__ __forceinline__ void wg_gemm(float (&d)[8][4], const uint32_t (&a)[16], uint32_t waddr, uint32_t accum) {
    const unsigned long long desc = (unsigned long long)((waddr & 0x3FFFFu) >> 4) | (1ull << 16) | (64ull << 32) | (1ull << 62);
    asm volatile("wgmma.fence.sync.aligned;" ::: "memory");
#pragma unroll
    for (int s = 0; s < 4; s++) {
        asm volatile("{ .reg .pred p; setp.ne.u32 p, %37, 0;"
                     " wgmma.mma_async.sync.aligned.m64n64k16.f32.bf16.bf16"
                     " {%0,%1,%2,%3,%4,%5,%6,%7,%8,%9,%10,%11,%12,%13,%14,%15,%16,%17,%18,%19,%20,%21,%22,%23,%24,%25,%26,%27,%28,%29,%30,%31},"
                     " {%32,%33,%34,%35}, %36, p, 1, 1, 1; }"
                     : "+f"(d[0][0]), "+f"(d[0][1]), "+f"(d[0][2]), "+f"(d[0][3]), "+f"(d[1][0]), "+f"(d[1][1]), "+f"(d[1][2]), "+f"(d[1][3]),
                       "+f"(d[2][0]), "+f"(d[2][1]), "+f"(d[2][2]), "+f"(d[2][3]), "+f"(d[3][0]), "+f"(d[3][1]), "+f"(d[3][2]), "+f"(d[3][3]),
                       "+f"(d[4][0]), "+f"(d[4][1]), "+f"(d[4][2]), "+f"(d[4][3]), "+f"(d[5][0]), "+f"(d[5][1]), "+f"(d[5][2]), "+f"(d[5][3]),
                       "+f"(d[6][0]), "+f"(d[6][1]), "+f"(d[6][2]), "+f"(d[6][3]), "+f"(d[7][0]), "+f"(d[7][1]), "+f"(d[7][2]), "+f"(d[7][3])
                     : "r"(a[4 * s]), "r"(a[4 * s + 1]), "r"(a[4 * s + 2]), "r"(a[4 * s + 3]), "l"(desc + s * 128), "r"(s ? 1u : accum)
                     : "memory");
    }
    asm volatile("wgmma.commit_group.sync.aligned;" ::: "memory");
    asm volatile("wgmma.wait_group.sync.aligned 0;"
                 : "+f"(d[0][0]), "+f"(d[0][1]), "+f"(d[0][2]), "+f"(d[0][3]), "+f"(d[1][0]), "+f"(d[1][1]), "+f"(d[1][2]), "+f"(d[1][3]),
                   "+f"(d[2][0]), "+f"(d[2][1]), "+f"(d[2][2]), "+f"(d[2][3]), "+f"(d[3][0]), "+f"(d[3][1]), "+f"(d[3][2]), "+f"(d[3][3]),
                   "+f"(d[4][0]), "+f"(d[4][1]), "+f"(d[4][2]), "+f"(d[4][3]), "+f"(d[5][0]), "+f"(d[5][1]), "+f"(d[5][2]), "+f"(d[5][3]),
                   "+f"(d[6][0]), "+f"(d[6][1]), "+f"(d[6][2]), "+f"(d[6][3]), "+f"(d[7][0]), "+f"(d[7][1]), "+f"(d[7][2]), "+f"(d[7][3])
                 :: "memory");
}
__device__ __forceinline__ void undef_acc(float (&d)[8][4]) {
#pragma unroll
    for (int j = 0; j < 8; j++) asm volatile("" : "=f"(d[j][0]), "=f"(d[j][1]), "=f"(d[j][2]), "=f"(d[j][3]));
}
__device__ __forceinline__ void to_afrag(uint32_t (&a)[16], const float (&d)[8][4]) {
#pragma unroll
    for (int j = 0; j < 8; j++) {
        a[2 * j] = pack_bf16(d[j][0], d[j][1]);
        a[2 * j + 1] = pack_bf16(d[j][2], d[j][3]);
    }
}
__device__ __forceinline__ void to_afrag(uint32_t (&a)[16], const float (&d)[8][4], float s_lo, float s_hi) {
#pragma unroll
    for (int j = 0; j < 8; j++) {
        a[2 * j] = pack_bf16(d[j][0] * s_lo, d[j][1] * s_lo);
        a[2 * j + 1] = pack_bf16(d[j][2] * s_hi, d[j][3] * s_hi);
    }
}

template <bool FIRST>
__device__ __forceinline__ void agg_chunk(float (&acc)[8][4], uint32_t la, int ofs, uint32_t a0, uint32_t a1, uint32_t a2, uint32_t a3) {
#pragma unroll
    for (int q = 0; q < 4; q++) {
        uint32_t b[4];
        ldsm4t(b, (la ^ (q << 5)) + ofs);
        if (FIRST) {
            mma16816_z(acc[2 * q], a0, a1, a2, a3, b[0], b[1]);
            mma16816_z(acc[2 * q + 1], a0, a1, a2, a3, b[2], b[3]);
        } else {
            mma16816(acc[2 * q], a0, a1, a2, a3, b[0], b[1]);
            mma16816(acc[2 * q + 1], a0, a1, a2, a3, b[2], b[3]);
        }
    }
}
template <int BIN>
__device__ __forceinline__ void cp16_ent(uint32_t dst, const char* xl, uint32_t e) {
    if (BIN >= 3)
        asm volatile("{ .reg .pred p; .reg .b64 a; .reg .b32 u; setp.ne.u32 p, %2, 0xFFFF; and.b32 u, %2, 0xFFF0; mad.wide.u32 a, u, 8, %1;"
                     " @p cp.async.cg.shared.global [%0], [a + %3], 16; }"
                     :: "r"(dst), "l"(xl), "r"(e), "n"(BIN * CLW * 128) : "memory");
    else if (BIN < 0)
        asm volatile("{ .reg .pred p; .reg .b64 a; .reg .b32 u; setp.ne.u32 p, %2, 0xFFFF; shr.u32 u, %2, 16; mad.wide.u32 a, u, 128, %1;"
                     " @p cp.async.cg.shared.global [%0], [a], 16; }"
                     :: "r"(dst), "l"(xl), "r"(e) : "memory");
    else
    if (BIN >= 0)
        asm volatile("{ .reg .pred p; .reg .b64 a; .reg .b32 u; setp.eq.u32 p, %2, 0xFFFF; and.b32 u, %2, 0xFFF0; mad.wide.u32 a, u, 8, %1;"
                     " cp.async.cg.shared.global [%0], [a + %3], 16, p; }"
                     :: "r"(dst), "l"(xl), "r"(e), "n"(BIN * CLW * 128) : "memory");
    else
        asm volatile("{ .reg .pred p; .reg .b64 a; .reg .b32 u; setp.eq.u32 p, %2, 0xFFFF; shr.u32 u, %2, 16; mad.wide.u32 a, u, 128, %1;"
                     " cp.async.cg.shared.global [%0], [a], 16, p; }"
                     :: "r"(dst), "l"(xl), "r"(e) : "memory");
}
template <int BIN>
__device__ __forceinline__ void issue_list(uint32_t da, int ofs, uint32_t ra, const char* xl) {
    const uint4 p = lds128(ra);
    const uint32_t db = da ^ 0x90u;
    cp16_ent<BIN>(da + ofs, xl, p.x);
    cp16_ent<BIN>(db + ofs, xl, p.y);
    cp16_ent<BIN>(da + ofs + 1024, xl, p.z);
    cp16_ent<BIN>(db + ofs + 1024, xl, p.w);
    cp_commit();
}
template <bool FIRST>
__device__ __forceinline__ void local_chunk(float (&acc)[8][4], uint32_t la, int ofs, uint32_t rt, uint32_t code) {
    const uint4 p = lds128(rt);
    const uint32_t w01 = prmt(p.x, p.y, 0x7632), w23 = prmt(p.z, p.w, 0x7632);
    uint32_t r01 = prmt(p.x, p.y, 0x5410), r23 = prmt(p.z, p.w, 0x5410);
    asm("lop3.b32 %0, %0, %1, 0x000F000F, 0xE4;" : "+r"(r01) : "r"(code));
    asm("lop3.b32 %0, %0, %1, 0x000F000F, 0xE4;" : "+r"(r23) : "r"(code));
    agg_chunk<FIRST>(acc, la, ofs, w01 & eq_lo2(r01, code), w01 & eq_hi2(r01, code), w23 & eq_lo2(r23, code), w23 & eq_hi2(r23, code));
}
__device__ __forceinline__ void store_tile(void* base, int tile, int lane, const uint32_t (&af)[16]) {
    if (tile < N_TILES) {
        char* orow = reinterpret_cast<char*>(base) + (size_t)(tile * 16 + (lane >> 2)) * 128 + (lane & 3) * 16;
        *reinterpret_cast<uint4*>(orow) = make_uint4(af[0], af[2], af[4], af[6]);
        *reinterpret_cast<uint4*>(orow + 64) = make_uint4(af[8], af[10], af[12], af[14]);
        *reinterpret_cast<uint4*>(orow + 1024) = make_uint4(af[1], af[3], af[5], af[7]);
        *reinterpret_cast<uint4*>(orow + 1024 + 64) = make_uint4(af[9], af[11], af[13], af[15]);
    }
}
__device__ __forceinline__ void attn_chunk(uint32_t (&y)[16], float& d0, float& d1, const uint32_t (&tq)[16], uint32_t lb, int lane) {
    float s0[4], s1[4];
    uint32_t xe[16];
#pragma unroll
    for (int s = 0; s < 4; s++) {
        ldsm4(xe[4 * s], xe[4 * s + 2], xe[4 * s + 1], xe[4 * s + 3], lb ^ (s << 5));
        if (s == 0) {
            mma16816_z(s0, tq[0], tq[1], tq[2], tq[3], xe[0], xe[2]);
            mma16816_z(s1, tq[0], tq[1], tq[2], tq[3], xe[1], xe[3]);
        } else {
            mma16816(s0, tq[4 * s], tq[4 * s + 1], tq[4 * s + 2], tq[4 * s + 3], xe[4 * s], xe[4 * s + 2]);
            mma16816(s1, tq[4 * s], tq[4 * s + 1], tq[4 * s + 2], tq[4 * s + 3], xe[4 * s + 1], xe[4 * s + 3]);
        }
    }
    const bool odd = lane & 4;
    const float p0 = ex2(odd ? s0[1] : s0[0]), p1 = ex2(odd ? s1[3] : s1[2]);
    d0 += p0;
    d1 += p1;
    const uint32_t p = __shfl_sync(~0u, pack_bf16(p0, p1), (lane & 28) | (lane >> 3));
    const uint32_t q0 = prmt(p, p, 0x1010), q1 = prmt(p, p, 0x3232);
#pragma unroll
    for (int i = 0; i < 16; i++) y[i] = fma_bf2(xe[i], (i & 1) ? q1 : q0, y[i]);
}
constexpr float QSCALE = 0.125f * 1.4426950408889634f;
__device__ __noinline__ void slow_cta(const __nv_bfloat16* x, const int* src, const int* dst, const int* esrc, const int* edst,
                                      const __nv_bfloat16* dis, const __nv_bfloat16* wl, const __nv_bfloat16* wq,
                                      const __nv_bfloat16* wk, const __nv_bfloat16* wv, __nv_bfloat16* out, unsigned char* smem) {
    constexpr int QCAP = 64;
    const int tid = threadIdx.x, lane = tid & 31, warp = tid >> 5, cta = blockIdx.x;
    const int tile = cta * NW + warp;
    float2* acc = reinterpret_cast<float2*>(smem + warp * 8192) + lane;
    float2* aux = acc + 512;
    uint32_t* queue = reinterpret_cast<uint32_t*>(smem + NW * 8192);
    uint32_t* cnt = queue + NW * QCAP;
    static_assert(NW * 8192 + NW * QCAP * 4 + NW * 4 <= SM_TOTAL, "slow path scratch");
    const uint32_t* xw = reinterpret_cast<const uint32_t*>(x) + lane;
    auto lo = [](uint32_t v) { return __uint_as_float(v << 16); };
    auto hi = [](uint32_t v) { return __uint_as_float(v & 0xFFFF0000u); };
    auto matvec = [&](float v0, float v1, const __nv_bfloat16* w, int sk, int sn) {
        float2 r = make_float2(0.f, 0.f);
#pragma unroll 1
        for (int k = 0; k < 64; k++) {
            const float a = __shfl_sync(~0u, (k & 1) ? v1 : v0, k >> 1);
            r.x += a * __bfloat162float(w[k * sk + 2 * lane * sn]);
            r.y += a * __bfloat162float(w[k * sk + (2 * lane + 1) * sn]);
        }
        return r;
    };
    cp_wait<0>();
    __syncthreads();
    if (tid < NW) cnt[tid] = 0u;
#pragma unroll 1
    for (int r = 0; r < 16; r++) {
        const uint32_t v = __ldg(xw + (size_t)(min(tile, N_TILES - 1) * 16 + r) * 32);
        const float2 q = matvec(lo(v), hi(v), wq, 64, 1);
        aux[r * 32] = matvec(q.x * QSCALE, q.y * QSCALE, wk, 1, 64);
    }
    __syncthreads();
#pragma unroll 1
    for (int pass = 0; pass < 2; pass++) {
        const int* dl = pass ? dst : edst;
        const int* sl = pass ? src : esrc;
        const int ne = pass ? N_EDGES : N_XEDGES;
        float den = 0.f;
#pragma unroll 1
        for (int r = 0; r < 16; r++) acc[r * 32] = make_float2(0.f, 0.f);
        int dnext = __ldg(dl + tid);
#pragma unroll 1
        for (int e = tid; e - tid < ne; e += NT) {
            const uint32_t loc = (uint32_t)(dnext - cta * NPC);
            bool pend = e < ne && loc < (uint32_t)NPC;
            if (e + NT < ne) dnext = __ldg(dl + e + NT);
            int more;
            do {
                if (pend) {
                    const uint32_t pos = atomicAdd(cnt + (loc >> 4), 1u);
                    if (pos < (uint32_t)QCAP) { queue[(loc >> 4) * QCAP + pos] = (uint32_t)e * 16u + (loc & 15u); pend = false; }
                }
                more = __syncthreads_or(pend);
                if (more || e - tid + NT >= ne) {
                    const int n = min((int)cnt[warp], QCAP);
#pragma unroll 1
                    for (int c = 0; c < n; c++) {
                        const uint32_t q = queue[warp * QCAP + c], r = q & 15u;
                        const int s = __ldg(sl + (q >> 4));
                        const uint32_t v = __ldg(xw + (size_t)s * 32);
                        float w;
                        if (pass) {
                            w = __bfloat162float(dis[s]);
                        } else {
                            const float2 t = aux[r * 32];
                            w = t.x * lo(v) + t.y * hi(v);
#pragma unroll
                            for (int o = 16; o; o >>= 1) w += __shfl_xor_sync(~0u, w, o);
                            w = ex2(w);
                            if (lane == (int)r) den += w;
                        }
                        float2 a = acc[r * 32];
                        a.x += w * lo(v);
                        a.y += w * hi(v);
                        acc[r * 32] = a;
                    }
                    __syncwarp();
                    if (lane == 0) cnt[warp] = 0u;
                    __syncthreads();
                }
            } while (more);
        }
#pragma unroll 1
        for (int r = 0; r < 16; r++) {
            const int node = min(tile, N_TILES - 1) * 16 + r;
            const float sc = pass ? __bfloat162float(dis[node]) : 1.f / (__shfl_sync(~0u, den, r) + 1e-9f);
            const float2 a = acc[r * 32];
            const float2 o = matvec(a.x * sc, a.y * sc, pass ? wl : wv, 64, 1);
            if (pass == 0) aux[r * 32] = o;
            else if (tile < N_TILES) reinterpret_cast<uint32_t*>(out)[node * 32 + lane] = pack_bf16(o.x + aux[r * 32].x, o.y + aux[r * 32].y);
        }
    }
}

__device__ __forceinline__ void post2(uint32_t ea) {
    const uint2 dv = lds64(ea), sv = lds64(ea + EC);
    const uint32_t d[2] = {dv.x, dv.y}, s[2] = {sv.x, sv.y};
    uint32_t b[2], a[2];
#pragma unroll
    for (int i = 0; i < 2; i++) {
        b[i] = __umulhi(d[i], 11184811u);
        a[i] = atoms_add(sb + SM_HIST + b[i] * 4, 4u);
    }
#pragma unroll
    for (int i = 0; i < 2; i++) sts32(a[i], prmt(d[i] - b[i] * NPC, s[i], 0x5410));
}
__device__ __forceinline__ void place4(const uint4& r) {
    const uint32_t v[4] = {r.x, r.y, r.z, r.w};
    uint32_t t[4], c[4], e[4];
#pragma unroll
    for (int i = 0; i < 4; i++) {
        const uint32_t k = __umulhi(v[i], 22u);
        t[i] = (v[i] & 0x1F0u) * 5u;
        c[i] = atoms_add(sb + SM_CNT + t[i] + k * 4u, 0x20004u);
        const uint32_t w = lds16(sb + SM_TABLE + (v[i] >> 15));
        e[i] = (v[i] >> 12) - k * (CLW * 16u);
        asm("lop3.b32 %0, %1, %0, 15, 0xE4;" : "+r"(e[i]) : "r"(v[i]));
        e[i] = prmt(e[i], w, 0x5410);
    }
#pragma unroll
    for (int i = 0; i < 4; i++)
        asm volatile("{ .reg .pred p; setp.ge.s32 p, %0, 0x200000; and.b32 %0, %0, 0x1FFFF; @p atom.shared.add.u32 %0, [%1 + %3], 4;"
                     " @p min.u32 %0, %0, %4; @p st.shared.u32 [%0 + %5], %2; }"
                     : "+r"(c[i]) : "r"(t[i]), "r"(v[i]), "n"(sb + SM_CNT + 76), "n"(sb + SM_BIN + (NW - 1) * TS + L_TS), "n"(TCAP * 4) : "memory");
#pragma unroll
    for (int i = 0; i < 4; i++) sts32(c[i], e[i]);
}
__device__ __forceinline__ bool is_null(uint32_t v) { return (~v & 0x180u) == 0u; }
__device__ __forceinline__ void wait_count(const uint32_t* p, uint32_t tagw) {
    const uint32_t go = tagw == 0xE00u ? 0u : (tagw >> 9) * NCTA;
    uint32_t v;
    int it = 0;
#pragma unroll 1
    do {
        asm volatile("ld.relaxed.gpu.global.u32 %0, [%1];" : "=r"(v) : "l"(p) : "memory");
        if (++it > (1 << 22)) break;
    } while (v != go);
}
__device__ __forceinline__ void arrive_count(uint32_t* p) {
    asm volatile("red.relaxed.gpu.global.inc.u32 [%0], %1;" :: "l"(p), "n"(7 * NCTA - 1) : "memory");
}
__device__ __forceinline__ void mbar_init(uint32_t mbar) {
    asm volatile("mbarrier.init.shared.b64 [%0], 1;" :: "r"(mbar) : "memory");
}
__device__ __forceinline__ void mbar_wait(uint32_t mbar) {
    uint32_t ok;
    int it = 0;
    do {
        asm volatile("{ .reg .pred p; mbarrier.try_wait.parity.shared.b64 p, [%1], 0; selp.u32 %0, 1, 0, p; }" : "=r"(ok) : "r"(mbar) : "memory");
        if (++it > (1 << 22)) break;
    } while (!ok);
}
__device__ __forceinline__ void mbar_expect(uint32_t mbar, uint32_t bytes) {
    asm volatile("mbarrier.arrive.expect_tx.shared.b64 _, [%0], %1;" :: "r"(mbar), "r"(bytes) : "memory");
}
__device__ __forceinline__ void bulk_load(uint32_t dst, const void* src, uint32_t bytes, uint32_t mbar) {
    asm volatile("cp.async.bulk.shared::cluster.global.mbarrier::complete_tx::bytes [%0], [%1], %2, [%3];"
                 :: "r"(dst), "l"(src), "r"(bytes), "r"(mbar) : "memory");
}
__device__ __forceinline__ void load_wlv(const __nv_bfloat16* wl, const __nv_bfloat16* wv, int warp, int lane) {
    if (warp < 16) {
        const uint32_t e = sb + SM_W + 8192 + warp * 128 + (((((lane >> 2) & 4) | (lane & 3)) ^ (warp & 7)) << 4) + (lane & 12);
#pragma unroll
        for (int q = 0; q < 4; q++) {
            cp4(e + q * 2048, wl + (warp * 32 + lane) * 2 + q * 1024);
            cp4(e + q * 2048 + 8192, wv + (warp * 32 + lane) * 2 + q * 1024);
        }
    }
    cp_commit();
}

template <bool FAST>
__global__ void __launch_bounds__(NT, 1)
exphormer_kernel(const __nv_bfloat16* __restrict__ x, const int* __restrict__ src, const int* __restrict__ dst,
                 const int* __restrict__ esrc, const int* __restrict__ edst, const __nv_bfloat16* __restrict__ dis,
                 const __nv_bfloat16* __restrict__ wl, const __nv_bfloat16* __restrict__ wq,
                 const __nv_bfloat16* __restrict__ wk, const __nv_bfloat16* __restrict__ wv,
                 __nv_bfloat16* __restrict__ out) {
    extern __shared__ __align__(1024) unsigned char smem[];
    if (!FAST || (uint32_t)__cvta_generic_to_shared(smem) != sb) {
        slow_cta(x, src, dst, esrc, edst, dis, wl, wq, wk, wv, out, smem);
        return;
    }
    const int tid = threadIdx.x, cta = blockIdx.x;
    const int lane = tid & 31, warp = tid >> 5;
    PROF(0);
    PROFC(13);

    const bool prod = FAST && cta < NPROD;
    constexpr uint32_t MB_EDGE = sb + SM_MISC, MB_TAB = MB_EDGE + 32, MB_REC = MB_TAB + 8;
    if (FAST && tid == 224) {
#pragma unroll
        for (int i = 0; i < 6; i++) mbar_init(MB_EDGE + i * 8);
        asm volatile("fence.mbarrier_init.release.cluster;" ::: "memory");
        if (prod) {
#pragma unroll
            for (int i = 0; i < 4; i++) {
                mbar_expect(MB_EDGE + i * 8, 2 * EC);
                bulk_load(sb + SM_EDGE + i * 2 * EC, dst + cta * EC + i * (EC / 4), EC, MB_EDGE + i * 8);
                bulk_load(sb + SM_EDGE + i * 2 * EC + EC, src + cta * EC + i * (EC / 4), EC, MB_EDGE + i * 8);
            }
        }
    }
    if (warp >= 8) {
        const int i = tid - 256;
        const uint32_t d = sb + SM_W + 8192 + (i >> 3) * 128 + (((i ^ (i >> 3)) & 7) << 4);
        cp16(d, wq + i * 8);
        cp16(d + 8192, wk + i * 8);
    }
    if (FAST) {
        if (prod && tid < EX) {
            cp4(sb + SM_EXTRA + tid * 8, dst + NPROD * EC + cta * EX + tid);
            cp4(sb + SM_EXTRA + tid * 8 + 4, src + NPROD * EC + cta * EX + tid);
        }
        if (tid == 160) cp16(sb + SM_TAG, g_count);
        cp_commit();
        const uint32_t nul = ((tid + cta) & 15) * 0x0C000000u + NPC;
#pragma unroll
        for (int i = 0; i < STG / (NT * 16); i++) sts128(sb + SM_MB + tid * 16 + i * NT * 16, nul);
        const int k = tid - 136, t = k / 20;
        uint32_t v = sb + SM_BIN + t * TS + min(k - t * 20, NCLS) * 64;
        if (k < 0) v = tid < 4 ? 0u : sb + SM_MB + (tid - 4) * MBS;
        if (k >= NW * 20) v = 0xC0000000u + sb + SM_DUMP;
        if (tid < (SM_EXTRA - SM_WCNT) / 4) sts32(sb + SM_WCNT + tid * 4, v);
        PROF(21);
        __syncthreads();
        const int pw = (warp < 12 && cta * NPC + tid < N_NODES) ? (int)(PSCHED >> (warp * 4)) & 15 : -1;
#pragma unroll 1
        for (int j = 0; j < 4; j++) {
            if (prod) mbar_wait(MB_EDGE + j * 8);
            PROF(22 + j);
            if (pw == j) asm volatile("prefetch.global.L2 [%0];" :: "l"(x + (size_t)(cta * NPC + tid) * 64) : "memory");
            if (j == TABAT && tid == PFT) {
                const int nown = min(NPC, N_NODES - cta * NPC);
                mbar_expect(MB_TAB, N_NODES * 2 + nown * 2);
                bulk_load(sb + SM_TABLE, dis, N_NODES * 2, MB_TAB);
                bulk_load(sb + SM_DIS, dis + cta * NPC, nown * 2, MB_TAB);
            }
            if (prod) post2(sb + SM_EDGE + j * 2 * EC + tid * 8);
        }
        cp_wait<0>();
        if (prod && tid < EX) {
            const uint2 v = lds64(sb + SM_EXTRA + tid * 8);
            const uint32_t b = __umulhi(v.x, 11184811u);
            sts32(atoms_add(sb + SM_HIST + b * 4, 4u), prmt(v.x - b * NPC, v.y, 0x5410));
        }
        if (tid == 160) sts32(sb + SM_TAG, (lds32(sb + SM_TAG) / NCTA + 1u) << 9);
    } else {
        cp_commit();
        cp_wait<0>();
    }
    PROF(4);
    __syncthreads();
    const uint32_t tagw = lds32(sb + SM_TAG);
    PROF(5);
    PROFC(20);
    if (prod && tid < 756) {
        const int c18 = tid / 18, k18 = tid - c18 * 18;
        const uint32_t sa = sb + SM_MB + c18 * MBS + k18 * 16;
        unsigned char* go = g_rec + c18 * GBKT + cta * 288 + k18 * 16;
        uint4 v[4];
        uint32_t m[4];
#pragma unroll
        for (int i = 0; i < 4; i++)
            if (i < 3 || tid < (NCTA - 126) * 18) {
                v[i] = lds128(sa + i * 42 * MBS);
                m[i] = lds32(sa + i * 42 * MBS + 80);
            }
#pragma unroll
        for (int i = 0; i < 4; i++)
            if (i < 3 || tid < (NCTA - 126) * 18) {
                v[i].x |= tagw;
                if (k18 >= 13 && !is_null(m[i])) {
                    v[i].y |= 0x200u;
                    uint4 u = lds128(sa + i * 42 * MBS + 80);
                    u.x |= tagw;
                    st_pair(go + i * 42 * GBKT + GOD - cta * 192 - 13 * 16, u);
                }
                st_pair(go + i * 42 * GBKT, v[i]);
            }
        if (tid < NCTA && lds32(sb + SM_HIST + tid * 4) > sb + SM_MB + (tid + 1) * MBS) atoms_add(sb + SM_WCNT, 256u);
    }
    if (FAST && tid == PFT) arrive_count(g_count);
    PROF(6);
    const uint32_t l0 = sb + SM_BIN + warp * TS;
    if (FAST) {
#pragma unroll
        for (int i = 0; i < 4; i++) sts128(l0 + lane * 16 + i * 512, 0xFFFFu);
    }
    if (warp < 16) {
        const int mi = warp >> 2, jp = warp & 3;
        const uint32_t pa = sb + SM_W + 8192 + (mi * 16 + (lane & 15)) * 128 + (((lane >> 4) ^ (lane & 7)) << 4);
        const uint32_t pb = sb + SM_W + 2 * 8192 + (jp * 16 + (lane & 7) + (lane >> 4) * 8) * 128 + ((((lane >> 3) & 1) ^ (lane & 7)) << 4);
        float e0[4], e1[4];
#pragma unroll
        for (int s = 0; s < 4; s++) {
            uint32_t a[4], b[4];
            ldsm4(a[0], a[1], a[2], a[3], pa ^ (s << 5));
            ldsm4(b[0], b[1], b[2], b[3], pb ^ (s << 5));
            if (s == 0) { mma16816_z(e0, a[0], a[1], a[2], a[3], b[0], b[1]); mma16816_z(e1, a[0], a[1], a[2], a[3], b[2], b[3]); }
            else        { mma16816(e0, a[0], a[1], a[2], a[3], b[0], b[1]);   mma16816(e1, a[0], a[1], a[2], a[3], b[2], b[3]); }
        }
        const float sc = 0.125f * 1.4426950408889634f;
        stsm4(sb + SM_W + (mi * 16 + (lane & 15)) * 128 + (((jp * 2 + (lane >> 4)) ^ (lane & 7)) << 4),
              pack_bf16(e0[0] * sc, e0[1] * sc), pack_bf16(e0[2] * sc, e0[3] * sc),
              pack_bf16(e1[0] * sc, e1[1] * sc), pack_bf16(e1[2] * sc, e1[3] * sc));
    }
    PROF(3);
    __syncthreads();
    if (FAST && tid == PFT) {
        wait_count(g_count, tagw);
        mbar_expect(MB_REC, GOD);
        bulk_load(sb + SM_MB, g_rec + cta * GBKT, GOD, MB_REC);
    }
    PROF(19);
    load_wlv(wl, wv, warp, lane);
    if (warp < 16) {
        cp_wait<0>();
        fence_async();
    }
    PROF(16);

    {
        mbar_wait(MB_TAB);
        PROF(17);
        mbar_wait(MB_REC);
        PROF(7);
        int it = 0;
#pragma unroll 1
        for (int i = 0; i < 3; i++) {
            const int u = tid + i * NT;
            uint4 r = lds128(sb + SM_MB + u * 16);
#pragma unroll 1
            while ((r.x ^ tagw) & 0xE00u) {
                r = ld_pair(g_rec + cta * GBKT + u * 16);
                if (++it > (1 << 22)) break;
            }
            if (!is_null(r.x)) place4(r);
            if (r.y & 0x200u) {
                unsigned char* gq = g_rec + cta * GBKT + GOD + u * 16 - (u / 18) * 192 - 13 * 16;
#pragma unroll 1
                do {
                    r = ld_pair(gq);
                    if (++it > (1 << 22)) break;
                } while ((r.x ^ tagw) & 0xE00u);
                st_pair(gq, make_uint4(0u, 0u, 0u, 0u));
                place4(r);
            }
        }
    }
    PROF(11);
    __syncthreads();

    const int tile = cta * NW + warp;
    const int wl24 = min(lane, NW - 1);
    uint32_t tend = lds32(sb + SM_CNT + wl24 * 80 + 76);
    if (__any_sync(~0u, tend > sb + SM_BIN + wl24 * TS + L_TS)) {
        if (tid < 2) st_pair(g_flag + cta * 2 + tid, make_uint4(tagw | 1u, 0u, 0u, 0u));
        __syncthreads();
        if (tid < NCTA) sts32(sb + SM_FLAG + tid * 16, 0u);
    } else {
        const uint32_t st0 = sb + SM_STAGE + warp * 2048;
        const uint32_t da = st0 + (lane >> 3) * 256 + (((lane & 7) ^ ((lane >> 3) * 2)) << 4);
        const char* xl = reinterpret_cast<const char*>(x) + (lane & 7) * 16;
        uint32_t ra = l0 + (lane >> 3) * 16, so;
        issue_list<0>(da, 0, ra, xl);
        PROF(12);
        PROFC(1);
        issue_list<1>(da, STG, ra + 64, xl);
        issue_list<2>(da, 2 * STG, ra + 128, xl);
        tend = __shfl_sync(~0u, tend, warp);
        {
            float acc[8][4];
            uint32_t rt = l0 + (lane & 3) * 16;
            const uint32_t la = st0 + (lane & 15) * 128 + (((lane >> 4) ^ (lane & 7)) << 4);
            const uint32_t code = (uint32_t)(lane >> 2) * 0x10001u + 0x04080400u;
#define STEP(OFS, NXT, K)                                          \
            wsync();                                               \
            issue_list<(K) + 2>(da, OFS, ra + ((K) + 2) * 64, xl); \
            cp_wait<2>(); wsync();                                 \
            local_chunk<false>(acc, la, NXT, rt + (K) * 64, code);
            cp_wait<2>(); wsync();
            PROF(10);
            local_chunk<true>(acc, la, 0, rt, code);
            STEP(0, STG, 1)
            STEP(STG, 2 * STG, 2)
#pragma unroll 1
            for (int i = 0; i < 4; i++) {
                if (i == 2) {
                    wsync();
                    cp16(l0 + lane * 16, (lane < 16 ? esrc : edst - 64) + min(tile, N_TILES - 1) * 64 + lane * 4);
                }
                STEP(2 * STG, 0, 3)
                STEP(0, STG, 4)
                STEP(STG, 2 * STG, 5)
                rt += 192; ra += 192; xl += 3 * CLW * 128;
            }
#undef STEP
            xl -= 12 * CLW * 128;
            PROF(8);
            {
                const uint4 ev = lds128(l0 + lane * 16);
                const uint32_t node = min(tile, N_TILES - 1) * 16 + (lane & 15);
                if (lane < 16) {
                    const uint32_t a = l0 + L_AL + (lane & 6) * 8 + (lane & 1) * 4 + (lane & 8);
                    sts32(a, node << 16);
                    sts32(a + 64, ev.x << 16);
                    sts32(a + 128, ev.y << 16);
                    sts32(a + 192, ev.z << 16);
                    sts32(a + 256, ev.w << 16);
                }
                const uint32_t inc = __any_sync(~0u, lane >= 16 && (ev.x != node || ev.y != node || ev.z != node || ev.w != node)) ? 257u : 1u;
                uint32_t v = 0;
                if (lane == 0) v = atoms_add(sb + SM_WCNT, inc) + inc;
                v = __shfl_sync(~0u, v, 0);
                if ((v & 255u) == NW && lane < 2) st_pair(g_flag + cta * 2 + lane, make_uint4(lds32(sb + SM_TAG) | (v > 255u), 0u, 0u, 0u));
            }
            int left = tend - (l0 + L_TW);
            ra += L_TS - 768;
            so = 2 * STG;
#pragma unroll 1
            do {
                if ((uint32_t)(left + 63) < 64u) ra = l0 + L_AL + (lane >> 3) * 16;
                wsync();
                issue_list<-1>(da + so, 0, ra, xl);
                so = so == 2 * STG ? 0 : so + STG;
                cp_wait<2>(); wsync();
                local_chunk<false>(acc, la + so, 0, rt + 192, code);
                left -= 64; rt += 64; ra += 64;
            } while (left > -128);
            wsync();
            issue_list<-1>(da + so, 0, ra, xl);
            PROF(14);
            PROFC(2);
            uint32_t af[16];
            const uint32_t pd = sb + SM_DIS + warp * 32 + (lane >> 2) * 2;
            to_afrag(af, acc, __uint_as_float(lds16(pd) << 16), __uint_as_float(lds16(pd + 16) << 16));
            wg_gemm(acc, af, sb + SM_W + 8192, blockDim.y - 1u);
            to_afrag(af, acc);
#pragma unroll
            for (int i = 0; i < 4; i++) sts128v(l0 + lane * 16 + i * 512, af[4 * i], af[4 * i + 1], af[4 * i + 2], af[4 * i + 3]);
        }
        PROF(9);
        {
            const uint32_t lb = st0 + ((lane & 7) + (lane >> 4) * 8) * 128 + ((((lane >> 3) & 1) ^ (lane & 7)) << 4);
            uint32_t tq[16], y[16];
            float t[8][4];
            so = so == 2 * STG ? 0 : so + STG;
            cp_wait<2>(); wsync();
#pragma unroll
            for (int s = 0; s < 4; s++) ldsm4(y[4 * s], y[4 * s + 2], y[4 * s + 1], y[4 * s + 3], (lb + so) ^ (s << 5));
            wsync();
            issue_list<-1>(da + so, 0, ra + 64, xl);
            undef_acc(t);
            wg_gemm(t, y, sb + SM_W, 0u);
            to_afrag(tq, t);
            PROF(18);
#pragma unroll
            for (int i = 0; i < 16; i++) y[i] = 0u;
            float e0 = 0.f, e1 = 0.f;
#pragma unroll 1
            for (int j = 0; j < 4; j++) {
                so = so == 2 * STG ? 0 : so + STG;
                cp_wait<2>(); wsync();
                attn_chunk(y, e0, e1, tq, lb + so, lane);
                if (j == 0) {
                    wsync();
                    if (tid < NCTA) cp16(sb + SM_FLAG + tid * 16, g_flag + tid * 2);
                    issue_list<-1>(da + so, 0, ra + 128, xl);
                } else {
                    cp_commit();
                }
                PROF(26 + j);
            }
            const uint32_t rden = __shfl_sync(~0u, pack_bf16(__fdividef(1.f, e0 + 1e-9f), __fdividef(1.f, e1 + 1e-9f)), (lane & 28) | (lane >> 3));
            undef_acc(t);
            wg_gemm(t, y, sb + SM_W + 2 * 8192, 0u);
            to_afrag(tq, t);
            const uint32_t q0 = prmt(rden, rden, 0x1010), q1 = prmt(rden, rden, 0x3232);
#pragma unroll
            for (int i = 0; i < 4; i++) {
                const uint4 a = lds128(l0 + lane * 16 + i * 512);
                tq[4 * i] = fma_bf2(tq[4 * i], q0, a.x);
                tq[4 * i + 1] = fma_bf2(tq[4 * i + 1], q1, a.y);
                tq[4 * i + 2] = fma_bf2(tq[4 * i + 2], q0, a.z);
                tq[4 * i + 3] = fma_bf2(tq[4 * i + 3], q1, a.w);
            }
            store_tile(out, tile, lane, tq);
        }
    }
    PROF(15);
    PROFC(30);
    uint32_t f = 0;
    if (tid < NCTA) {
        const uint32_t tg = lds32(sb + SM_TAG);
        f = lds32(sb + SM_FLAG + tid * 16);
        int it = 0;
#pragma unroll 1
        while ((f ^ tg) > 1u) {
            asm volatile("ld.relaxed.gpu.global.u32 %0, [%1];" : "=r"(f) : "l"(g_flag + tid * 2) : "memory");
            if (++it > (1 << 22)) break;
        }
    }
    if (__builtin_expect(__syncthreads_or(f & 1u), 0)) slow_cta(x, src, dst, esrc, edst, dis, wl, wq, wk, wv, out, smem);
}

}

extern "C" void kernel_launch(void* const* d_in, const int* in_sizes, int n_in, void* d_out, int out_size) {
    (void)in_sizes; (void)n_in; (void)out_size;
    const __nv_bfloat16* x   = (const __nv_bfloat16*)d_in[0];
    const int* src           = (const int*)d_in[1];
    const int* dst           = (const int*)d_in[2];
    const int* esrc          = (const int*)d_in[3];
    const int* edst          = (const int*)d_in[4];
    const __nv_bfloat16* dis = (const __nv_bfloat16*)d_in[5];
    const __nv_bfloat16* wl  = (const __nv_bfloat16*)d_in[6];
    const __nv_bfloat16* wq  = (const __nv_bfloat16*)d_in[7];
    const __nv_bfloat16* wk  = (const __nv_bfloat16*)d_in[8];
    const __nv_bfloat16* wv  = (const __nv_bfloat16*)d_in[9];
    __nv_bfloat16* out = (__nv_bfloat16*)d_out;

    static int fast = -1;
    if (fast < 0) {
        cudaFuncSetAttribute(exphormer_kernel<true>, cudaFuncAttributeMaxDynamicSharedMemorySize, SM_TOTAL);
        cudaFuncSetAttribute(exphormer_kernel<false>, cudaFuncAttributeMaxDynamicSharedMemorySize, SM_TOTAL);
        int dev = 0, sms = 0, occ = 0;
        cudaGetDevice(&dev);
        cudaDeviceGetAttribute(&sms, cudaDevAttrMultiProcessorCount, dev);
        cudaOccupancyMaxActiveBlocksPerMultiprocessor(&occ, exphormer_kernel<true>, NT, SM_TOTAL);
        fast = (sms * occ >= NCTA) ? 1 : 0;
    }
    if (fast) exphormer_kernel<true><<<NCTA, NT, SM_TOTAL>>>(x, src, dst, esrc, edst, dis, wl, wq, wk, wv, out);
    else      exphormer_kernel<false><<<NCTA, NT, SM_TOTAL>>>(x, src, dst, esrc, edst, dis, wl, wq, wk, wv, out);
}
```

```cpp
#include <cuda_runtime.h>
#include <cuda.h>
#include <cuda_bf16.h>
#include <stdint.h>

namespace {

constexpr int PIECE = 256;
constexpr int XD = 150;
constexpr int TH0 = 8100;
constexpr int JMAX = 3;
constexpr int TE = 1760;
constexpr int CI = 3;
constexpr int PP = 2340;
constexpr int CA = 350;
constexpr int ST = 16;
constexpr int TD = 2300;
constexpr int PB = 2750;
constexpr int HEAD = 128;
constexpr int KC = 161;
constexpr int SWZ = 0x60;
constexpr int TW = 3000;
constexpr int N_NODES  = 50000;
constexpr int N_EDGES  = 800000;
constexpr int N_XEDGES = 200000;
constexpr int N_TILES  = N_NODES / 16;
constexpr int NW       = 24;
constexpr int NT       = NW * 32;
constexpr int NPC      = NW * 16;
constexpr int NCTA     = (N_NODES + NPC - 1) / NPC;
constexpr int NPROD    = NT / 6;
constexpr int EC       = NT * 8;
constexpr int EX       = N_EDGES / NPROD - EC;
constexpr int MBS      = 352 ;
constexpr int NMORE    = (MBS - PIECE) / 16;
constexpr int G2       = NT * 16;
constexpr int GOD      = NPROD * PIECE;
constexpr int GBKT     = NPROD * MBS;
constexpr int NCLS     = 17;
constexpr int HODD     = (N_NODES + 127) / 128;
constexpr uint32_t CMUL = KC * (1ull << 27) / (HODD * 1280);
constexpr int TL       = 528, TCAP = 448;
constexpr int TS       = 2224;
constexpr int BP       = 272;
constexpr int NTH      = NT + 128;
constexpr int STG      = NW * 2048;

static_assert(NPROD * (EC + EX) == N_EDGES && EX <= NT && NPROD <= NCTA && N_NODES % 16 == 0 && NPROD == 128, "edge slices");
static_assert(NCLS == 17 && HODD * 64 * CMUL >> 27 == 8 && HODD * 128 < 0xFFFF && NPC % 128 == 0, "classes");

constexpr int SM_BIN   = 0;
constexpr int SM_EDGE  = SM_BIN;
constexpr int SM_ES    = SM_EDGE + EC * 8;
constexpr int SM_NULL  = SM_BIN + NW * TS;
constexpr int SM_STAGE = 54 * 1024;
constexpr int SM_QK    = SM_STAGE + STG;
constexpr int SM_MB    = SM_STAGE + 2 * STG;
constexpr int SM_W     = SM_STAGE + 3 * STG;
constexpr int SM_DIS   = SM_W + 3 * 8192;
constexpr int SM_MISC  = SM_DIS + NPC * 2;
constexpr int SM_TAG   = SM_MISC + 80;
constexpr int SM_CUR   = SM_TAG + 16;
constexpr int SM_WCNT  = SM_CUR + NCLS * 128 + 124;
constexpr int SM_HIST  = SM_CUR + (NCLS + 1) * 128;
constexpr int SM_EXTRA = SM_HIST + 2 * 132 * 4;
constexpr int SM_TOTAL = SM_EXTRA + (EX + 2) * 8 + 32;
constexpr int SM_LAST  = SM_W + TL;
constexpr int SM_RUN   = SM_W + NW * TL;
constexpr int TP       = 112;
constexpr int SM_DUMP  = SM_HIST;
constexpr uint32_t sb  = 1024;
static_assert(SM_NULL + 80 <= SM_STAGE && SM_NULL % 16 == 0 && SM_MISC % 16 == 0 && SM_TOTAL <= 232448 && SM_EXTRA % 16 == 0 && EX % 4 == 2, "layout");
static_assert(SM_ES + NW * 256 <= SM_STAGE && NCTA * MBS <= STG && MBS + 128 <= 2 * 132 * 4, "layout");
static_assert(GOD <= 3 * G2 && GOD > 2 * G2 && NMORE % 2 == 0 && MBS % 16 == 0 && PIECE % 32 == 0, "inbox");
static_assert(NPROD * MBS <= NW * TS && (EC + EX + 2) * 4 + HEAD <= 3 * 8192 + MBS + STG - NCTA * MBS, "runaway cursors stay clear of the control data");

static_assert(8 * BP <= TS && SM_RUN + NW * TP <= SM_W + 2 * 8192 && TCAP + 64 <= TL && 5 + 3 * CI >= 8 && G2 <= NPROD * HEAD, "lists");

__device__ __align__(1024) unsigned char g_h[HODD * 128 * 128];
__device__ __align__(128) unsigned char g_rec[NCTA * GBKT];
__device__ __align__(128) uint4 g_flag[NCTA * 2];
__device__ __align__(128) uint32_t g_count[96];
constexpr uint32_t TAGM = 0x300000u, NUL = 0xFFFFu;

__device__ __forceinline__ void mma16816(float (&d)[4], uint32_t a0, uint32_t a1, uint32_t a2, uint32_t a3,
                                         uint32_t b0, uint32_t b1) {
    asm volatile("mma.sync.aligned.m16n8k16.row.col.f32.bf16.bf16.f32 {%0,%1,%2,%3}, {%4,%5,%6,%7}, {%8,%9}, {%0,%1,%2,%3};"
                 : "+f"(d[0]), "+f"(d[1]), "+f"(d[2]), "+f"(d[3])
                 : "r"(a0), "r"(a1), "r"(a2), "r"(a3), "r"(b0), "r"(b1));
}
__device__ __forceinline__ void mma16816_z(float (&d)[4], uint32_t a0, uint32_t a1, uint32_t a2, uint32_t a3,
                                           uint32_t b0, uint32_t b1) {
    asm volatile("mma.sync.aligned.m16n8k16.row.col.f32.bf16.bf16.f32 {%0,%1,%2,%3}, {%4,%5,%6,%7}, {%8,%9}, {%10,%10,%10,%10};"
                 : "=f"(d[0]), "=f"(d[1]), "=f"(d[2]), "=f"(d[3])
                 : "r"(a0), "r"(a1), "r"(a2), "r"(a3), "r"(b0), "r"(b1), "f"(0.f));
}
__device__ __forceinline__ void ldsm4(uint32_t& r0, uint32_t& r1, uint32_t& r2, uint32_t& r3, uint32_t addr) {
    asm volatile("ldmatrix.sync.aligned.m8n8.x4.shared.b16 {%0,%1,%2,%3}, [%4];"
                 : "=r"(r0), "=r"(r1), "=r"(r2), "=r"(r3) : "r"(addr) : "memory");
}
__device__ __forceinline__ void ldsm4t(uint32_t (&r)[4], uint32_t addr) {
    asm volatile("ldmatrix.sync.aligned.m8n8.x4.trans.shared.b16 {%0,%1,%2,%3}, [%4];"
                 : "=r"(r[0]), "=r"(r[1]), "=r"(r[2]), "=r"(r[3]) : "r"(addr) : "memory");
}
__device__ __forceinline__ void stsm4(uint32_t addr, uint32_t r0, uint32_t r1, uint32_t r2, uint32_t r3) {
    asm volatile("stmatrix.sync.aligned.m8n8.x4.shared.b16 [%0], {%1,%2,%3,%4};"
                 :: "r"(addr), "r"(r0), "r"(r1), "r"(r2), "r"(r3) : "memory");
}
__device__ __forceinline__ uint32_t pack_bf16(float lo, float hi) {
    uint32_t r;
    asm("cvt.rn.bf16x2.f32 %0, %1, %2;" : "=r"(r) : "f"(hi), "f"(lo));
    return r;
}
__device__ __forceinline__ uint32_t fma_bf2(uint32_t a, uint32_t b, uint32_t c) {
    uint32_t r;
    asm volatile("fma.rn.bf16x2 %0, %1, %2, %3;" : "=r"(r) : "r"(a), "r"(b), "r"(c));
    return r;
}
__device__ __forceinline__ uint32_t prmt(uint32_t a, uint32_t b, uint32_t s) {
    uint32_t r;
    asm("prmt.b32 %0, %1, %2, %3;" : "=r"(r) : "r"(a), "r"(b), "r"(s));
    return r;
}
__device__ __forceinline__ uint32_t eq_lo2(uint32_t a, uint32_t b) {
    uint32_t r;
    asm("{ .reg .b16 l, h; .reg .b32 c; mov.b32 {l, h}, %2; mov.b32 c, {l, l}; set.eq.u32.f16x2 %0, %1, c; }" : "=r"(r) : "r"(a), "r"(b));
    return r;
}
__device__ __forceinline__ uint32_t eq_hi2(uint32_t a, uint32_t b) {
    uint32_t r;
    asm("{ .reg .b16 l, h; .reg .b32 c; mov.b32 {l, h}, %2; mov.b32 c, {h, h}; set.eq.u32.f16x2 %0, %1, c; }" : "=r"(r) : "r"(a), "r"(b));
    return r;
}
__device__ __forceinline__ float ex2(float x) {
    float r;
    asm("ex2.approx.ftz.f32 %0, %1;" : "=f"(r) : "f"(x));
    return r;
}
__device__ __forceinline__ void cp16(uint32_t dst, const void* src) {
    asm volatile("cp.async.cg.shared.global [%0], [%1], 16;" :: "r"(dst), "l"(src) : "memory");
}
__device__ __forceinline__ void cp4(uint32_t dst, const void* src) {
    asm volatile("cp.async.ca.shared.global [%0], [%1], 4;" :: "r"(dst), "l"(src) : "memory");
}
__device__ __forceinline__ void cp_commit() { asm volatile("cp.async.commit_group;" ::: "memory"); }
template <int N> __device__ __forceinline__ void cp_wait() { asm volatile("cp.async.wait_group %0;" :: "n"(N) : "memory"); }
__device__ __forceinline__ void fence_async() { asm volatile("fence.proxy.async.shared::cta;" ::: "memory"); }
template <int ID, int N> __device__ __forceinline__ void bar_sync() { asm volatile("bar.sync %0, %1;" :: "n"(ID), "n"(N) : "memory"); }
template <int ID, int N> __device__ __forceinline__ void bar_arrive() { asm volatile("bar.arrive %0, %1;" :: "n"(ID), "n"(N) : "memory"); }
__device__ __forceinline__ int bar_or(int v) {
    int r;
    asm volatile("{ .reg .pred p; setp.ne.s32 p, %1, 0; bar.red.or.pred p, 0, %2, p; selp.s32 %0, 1, 0, p; }" : "=r"(r) : "r"(v), "n"(NT) : "memory");
    return r;
}
__device__ __forceinline__ void wsync() { asm volatile("bar.warp.sync 0xffffffff;" ::: "memory"); }
__device__ __forceinline__ uint4 lds128(uint32_t a) {
    uint4 v;
    asm volatile("ld.shared.v4.u32 {%0,%1,%2,%3}, [%4];" : "=r"(v.x), "=r"(v.y), "=r"(v.z), "=r"(v.w) : "r"(a) : "memory");
    return v;
}
__device__ __forceinline__ uint2 lds64(uint32_t a) {
    uint2 v;
    asm volatile("ld.shared.v2.u32 {%0,%1}, [%2];" : "=r"(v.x), "=r"(v.y) : "r"(a) : "memory");
    return v;
}
__device__ __forceinline__ uint32_t lds32(uint32_t a) {
    uint32_t v;
    asm volatile("ld.shared.u32 %0, [%1];" : "=r"(v) : "r"(a) : "memory");
    return v;
}
__device__ __forceinline__ uint32_t lds16(uint32_t a) {
    uint32_t v;
    asm volatile("ld.shared.u16 %0, [%1];" : "=r"(v) : "r"(a) : "memory");
    return v;
}
__device__ __forceinline__ void sts32(uint32_t a, uint32_t v) { asm volatile("st.shared.u32 [%0], %1;" :: "r"(a), "r"(v) : "memory"); }
__device__ __forceinline__ void sts128(uint32_t a, uint32_t v) {
    asm volatile("st.shared.v4.u32 [%0], {%1,%1,%1,%1};" :: "r"(a), "r"(v) : "memory");
}
__device__ __forceinline__ uint32_t atoms_add(uint32_t a, uint32_t v) {
    uint32_t r;
    asm volatile("atom.shared.add.u32 %0, [%1], %2;" : "=r"(r) : "r"(a), "r"(v) : "memory");
    return r;
}
__device__ __forceinline__ void sts128v(uint32_t a, uint32_t x, uint32_t y, uint32_t z, uint32_t w) {
    asm volatile("st.shared.v4.u32 [%0], {%1,%2,%3,%4};" :: "r"(a), "r"(x), "r"(y), "r"(z), "r"(w) : "memory");
}
__device__ __forceinline__ uint4 ld_pair(const void* p) {
    unsigned long long a, b;
    asm volatile("{ .reg .b128 t; ld.relaxed.gpu.global.b128 t, [%2]; mov.b128 {%0, %1}, t; }" : "=l"(a), "=l"(b) : "l"(p) : "memory");
    return make_uint4((uint32_t)a, (uint32_t)(a >> 32), (uint32_t)b, (uint32_t)(b >> 32));
}
__device__ __forceinline__ void st_pair(void* p, uint4 v) {
    const unsigned long long a = ((unsigned long long)v.y << 32) | v.x, b = ((unsigned long long)v.w << 32) | v.z;
    asm volatile("{ .reg .b128 t; mov.b128 t, {%1, %2}; st.relaxed.gpu.global.b128 [%0], t; }" :: "l"(p), "l"(a), "l"(b) : "memory");
}

template <bool TR = false, bool WAIT = true>
__device__ __forceinline__ void wg_gemm(float (&d)[8][4], const uint32_t (&a)[16], uint32_t waddr, uint32_t accum) {
    const unsigned long long desc = (unsigned long long)((waddr & 0x3FFFFu) >> 4) | (1ull << 16) | (64ull << 32) | (1ull << 62);
    asm volatile("wgmma.fence.sync.aligned;" ::: "memory");
#pragma unroll
    for (int s = 0; s < 4; s++) {
        asm volatile("{ .reg .pred p; setp.ne.u32 p, %37, 0;"
                     " wgmma.mma_async.sync.aligned.m64n64k16.f32.bf16.bf16"
                     " {%0,%1,%2,%3,%4,%5,%6,%7,%8,%9,%10,%11,%12,%13,%14,%15,%16,%17,%18,%19,%20,%21,%22,%23,%24,%25,%26,%27,%28,%29,%30,%31},"
                     " {%32,%33,%34,%35}, %36, p, 1, 1, %38; }"
                     : "+f"(d[0][0]), "+f"(d[0][1]), "+f"(d[0][2]), "+f"(d[0][3]), "+f"(d[1][0]), "+f"(d[1][1]), "+f"(d[1][2]), "+f"(d[1][3]),
                       "+f"(d[2][0]), "+f"(d[2][1]), "+f"(d[2][2]), "+f"(d[2][3]), "+f"(d[3][0]), "+f"(d[3][1]), "+f"(d[3][2]), "+f"(d[3][3]),
                       "+f"(d[4][0]), "+f"(d[4][1]), "+f"(d[4][2]), "+f"(d[4][3]), "+f"(d[5][0]), "+f"(d[5][1]), "+f"(d[5][2]), "+f"(d[5][3]),
                       "+f"(d[6][0]), "+f"(d[6][1]), "+f"(d[6][2]), "+f"(d[6][3]), "+f"(d[7][0]), "+f"(d[7][1]), "+f"(d[7][2]), "+f"(d[7][3])
                     : "r"(a[4 * s]), "r"(a[4 * s + 1]), "r"(a[4 * s + 2]), "r"(a[4 * s + 3]), "l"(desc + s * (TR ? 2 : 128)), "r"(s ? 1u : accum), "n"(TR ? 0 : 1)
                     : "memory");
    }
    asm volatile("wgmma.commit_group.sync.aligned;" ::: "memory");
    if (WAIT) asm volatile("wgmma.wait_group.sync.aligned 0;"
                 : "+f"(d[0][0]), "+f"(d[0][1]), "+f"(d[0][2]), "+f"(d[0][3]), "+f"(d[1][0]), "+f"(d[1][1]), "+f"(d[1][2]), "+f"(d[1][3]),
                   "+f"(d[2][0]), "+f"(d[2][1]), "+f"(d[2][2]), "+f"(d[2][3]), "+f"(d[3][0]), "+f"(d[3][1]), "+f"(d[3][2]), "+f"(d[3][3]),
                   "+f"(d[4][0]), "+f"(d[4][1]), "+f"(d[4][2]), "+f"(d[4][3]), "+f"(d[5][0]), "+f"(d[5][1]), "+f"(d[5][2]), "+f"(d[5][3]),
                   "+f"(d[6][0]), "+f"(d[6][1]), "+f"(d[6][2]), "+f"(d[6][3]), "+f"(d[7][0]), "+f"(d[7][1]), "+f"(d[7][2]), "+f"(d[7][3])
                 :: "memory");
}
__device__ __forceinline__ void wg_wait(float (&d)[8][4], const uint32_t (&a)[16]) {
    asm volatile("wgmma.wait_group.sync.aligned 0;"
                 : "+f"(d[0][0]), "+f"(d[0][1]), "+f"(d[0][2]), "+f"(d[0][3]), "+f"(d[1][0]), "+f"(d[1][1]), "+f"(d[1][2]), "+f"(d[1][3]),
                   "+f"(d[2][0]), "+f"(d[2][1]), "+f"(d[2][2]), "+f"(d[2][3]), "+f"(d[3][0]), "+f"(d[3][1]), "+f"(d[3][2]), "+f"(d[3][3]),
                   "+f"(d[4][0]), "+f"(d[4][1]), "+f"(d[4][2]), "+f"(d[4][3]), "+f"(d[5][0]), "+f"(d[5][1]), "+f"(d[5][2]), "+f"(d[5][3]),
                   "+f"(d[6][0]), "+f"(d[6][1]), "+f"(d[6][2]), "+f"(d[6][3]), "+f"(d[7][0]), "+f"(d[7][1]), "+f"(d[7][2]), "+f"(d[7][3])
                 :: "memory");
}
__device__ __forceinline__ void undef_acc(float (&d)[8][4]) {
#pragma unroll
    for (int j = 0; j < 8; j++) asm volatile("" : "=f"(d[j][0]), "=f"(d[j][1]), "=f"(d[j][2]), "=f"(d[j][3]));
}
__device__ __forceinline__ void to_afrag(uint32_t (&a)[16], const float (&d)[8][4]) {
#pragma unroll
    for (int j = 0; j < 8; j++) {
        a[2 * j] = pack_bf16(d[j][0], d[j][1]);
        a[2 * j + 1] = pack_bf16(d[j][2], d[j][3]);
    }
}
__device__ __forceinline__ void to_afrag(uint32_t (&a)[16], const float (&d)[8][4], float s_lo, float s_hi) {
#pragma unroll
    for (int j = 0; j < 8; j++) {
        a[2 * j] = pack_bf16(d[j][0] * s_lo, d[j][1] * s_lo);
        a[2 * j + 1] = pack_bf16(d[j][2] * s_hi, d[j][3] * s_hi);
    }
}

template <bool ZERO>
__device__ __forceinline__ void cp16_ent(uint32_t dst, const char* xl, uint32_t e) {
    const uint32_t u = ~e & 0xFFFFu;
    if (ZERO)
        asm volatile("{ .reg .pred p; .reg .b64 a; setp.eq.u32 p, %2, 0; mul.wide.s32 a, %2, -128; add.s64 a, %1, a;"
                     " cp.async.cg.shared.global [%0], [a], 16, p; }" :: "r"(dst), "l"(xl), "r"(u) : "memory");
    else
        asm volatile("{ .reg .pred p; .reg .b64 a; setp.ne.u32 p, %2, 0; mul.wide.s32 a, %2, -128; add.s64 a, %1, a;"
                     " @p cp.async.cg.shared.global [%0], [a], 16; }" :: "r"(dst), "l"(xl), "r"(u) : "memory");
}
template <bool ZERO>
__device__ __forceinline__ void issue_list(uint32_t da, uint32_t db, const uint4& p, const char* xl) {
    cp16_ent<ZERO>(da, xl, p.x);
    cp16_ent<ZERO>(db, xl, p.y);
    cp16_ent<ZERO>(da + 1024, xl, p.z);
    cp16_ent<ZERO>(db + 1024, xl, p.w);
    cp_commit();
}
__device__ __forceinline__ void cp16_row(uint32_t dst, const char* xl, uint32_t row) {
    asm volatile("{ .reg .b64 a; mul.wide.u32 a, %2, 128; add.s64 a, %1, a; cp.async.cg.shared.global [%0], [a], 16; }"
                 :: "r"(dst), "l"(xl), "r"(row) : "memory");
}
__device__ __forceinline__ void issue_rows(uint32_t d, const char* xl, uint32_t r0, uint32_t r1, uint32_t r2, uint32_t r3) {
    cp16_row(d, xl, r0); cp16_row((d ^ 16u) + 128, xl, r1); cp16_row(d + 1024, xl, r2); cp16_row((d ^ 16u) + 1152, xl, r3);
    cp_commit();
}
__device__ __forceinline__ uint32_t pin(uint32_t v, uint32_t dep) {
    uint32_t r;
    asm volatile("lop3.b32 %0, %1, %2, %3, 0xF8;" : "=r"(r) : "r"(v), "r"(dep), "r"(blockDim.y - 1u));
    return r;
}
__device__ __forceinline__ uint32_t rows_of(const uint4& q, uint32_t from) {
    const uint32_t r = prmt(prmt(q.x, q.y, 0x0062), prmt(q.z, q.w, 0x0062), 0x5410) & 0x3F3F3F3Fu;
    return __shfl_sync(~0u, r, from);
}
__device__ __forceinline__ uint32_t now_clk() {
    uint32_t t;
    asm volatile("{ .reg .b64 c; mov.u64 c, %%clock64; cvt.u32.u64 %0, c; }" : "=r"(t) :: "memory");
    return t;
}
__device__ __forceinline__ void wait_clk(uint32_t t) {
    while (t - now_clk() < 16384u) {}
}
__device__ __forceinline__ void chunk(float (&acc)[8][4], const uint32_t (&la)[4], uint32_t ofs, uint32_t& r, uint32_t from, uint32_t code,
                                      uint32_t w0, uint32_t w1, uint32_t da, uint32_t db, const uint4& q, const char* xl, bool more = true) {
    const uint32_t r01 = prmt(r, code, 0x5150), r23 = prmt(r, code, 0x5352);
    const uint32_t a0 = w0 & eq_lo2(r01, code), a1 = w1 & eq_hi2(r01, code), a2 = w0 & eq_lo2(r23, code), a3 = w1 & eq_hi2(r23, code);
    uint32_t b[4][4];
    cp_wait<2>(); wsync();
#pragma unroll
    for (int i = 0; i < 4; i++) ldsm4t(b[i], la[i] + ofs);
    wsync();
    if (more) {
        issue_list<false>(da + ofs, db + ofs, q, xl);
        r = rows_of(q, from);
    } else {
        cp_commit();
    }
#pragma unroll
    for (int i = 0; i < 4; i++) {
        mma16816(acc[2 * i], a0, a1, a2, a3, b[i][0], b[i][1]);
        mma16816(acc[2 * i + 1], a0, a1, a2, a3, b[i][2], b[i][3]);
    }
}
__device__ __forceinline__ void store_tile(void* base, int tile, int lane, const uint32_t (&af)[16]) {
    if (tile < N_TILES) {
        char* orow = reinterpret_cast<char*>(base) + (size_t)(tile * 16 + (lane >> 2)) * 128 + (lane & 3) * 16;
        *reinterpret_cast<uint4*>(orow) = make_uint4(af[0], af[2], af[4], af[6]);
        *reinterpret_cast<uint4*>(orow + 64) = make_uint4(af[8], af[10], af[12], af[14]);
        *reinterpret_cast<uint4*>(orow + 1024) = make_uint4(af[1], af[3], af[5], af[7]);
        *reinterpret_cast<uint4*>(orow + 1024 + 64) = make_uint4(af[9], af[11], af[13], af[15]);
    }
}
__device__ __forceinline__ void attn_chunk(uint32_t (&y)[16], float& d0, float& d1, const uint32_t (&tq)[16], uint32_t lb, int lane) {
    float s0[4], s1[4];
    uint32_t xe[16];
#pragma unroll
    for (int s = 0; s < 4; s++) {
        ldsm4(xe[4 * s], xe[4 * s + 2], xe[4 * s + 1], xe[4 * s + 3], lb ^ (s << 5));
        if (s == 0) {
            mma16816_z(s0, tq[0], tq[1], tq[2], tq[3], xe[0], xe[2]);
            mma16816_z(s1, tq[0], tq[1], tq[2], tq[3], xe[1], xe[3]);
        } else {
            mma16816(s0, tq[4 * s], tq[4 * s + 1], tq[4 * s + 2], tq[4 * s + 3], xe[4 * s], xe[4 * s + 2]);
            mma16816(s1, tq[4 * s], tq[4 * s + 1], tq[4 * s + 2], tq[4 * s + 3], xe[4 * s + 1], xe[4 * s + 3]);
        }
    }
    const bool odd = lane & 4;
    const float p0 = ex2(odd ? s0[1] : s0[0]), p1 = ex2(odd ? s1[3] : s1[2]);
    d0 += p0;
    d1 += p1;
    const uint32_t p = __shfl_sync(~0u, pack_bf16(p0, p1), (lane & 28) | (lane >> 3));
    const uint32_t q0 = prmt(p, p, 0x1010), q1 = prmt(p, p, 0x3232);
#pragma unroll
    for (int i = 0; i < 16; i++) y[i] = fma_bf2(xe[i], (i & 1) ? q1 : q0, y[i]);
}
constexpr float QSCALE = 0.125f * 1.4426950408889634f;
__device__ __noinline__ void slow_cta(const __nv_bfloat16* x, const int* src, const int* dst, const int* esrc, const int* edst,
                                      const __nv_bfloat16* dis, const __nv_bfloat16* wl, const __nv_bfloat16* wq,
                                      const __nv_bfloat16* wk, const __nv_bfloat16* wv, __nv_bfloat16* out, unsigned char* smem) {
    constexpr int QCAP = 64;
    const int tid = threadIdx.x, lane = tid & 31, warp = tid >> 5, cta = blockIdx.x;
    const int tile = cta * NW + warp;
    float2* acc = reinterpret_cast<float2*>(smem + warp * 8192) + lane;
    float2* aux = acc + 512;
    uint32_t* queue = reinterpret_cast<uint32_t*>(smem + NW * 8192);
    uint32_t* cnt = queue + NW * QCAP;
    static_assert(NW * 8192 + NW * QCAP * 4 + NW * 4 <= SM_TOTAL, "slow path scratch");
    const uint32_t* xw = reinterpret_cast<const uint32_t*>(x) + lane;
    auto lo = [](uint32_t v) { return __uint_as_float(v << 16); };
    auto hi = [](uint32_t v) { return __uint_as_float(v & 0xFFFF0000u); };
    auto matvec = [&](float v0, float v1, const __nv_bfloat16* w, int sk, int sn) {
        float2 r = make_float2(0.f, 0.f);
#pragma unroll 1
        for (int k = 0; k < 64; k++) {
            const float a = __shfl_sync(~0u, (k & 1) ? v1 : v0, k >> 1);
            r.x += a * __bfloat162float(w[k * sk + 2 * lane * sn]);
            r.y += a * __bfloat162float(w[k * sk + (2 * lane + 1) * sn]);
        }
        return r;
    };
    cp_wait<0>();
    bar_sync<0, NT>();
    if (tid < NW) cnt[tid] = 0u;
#pragma unroll 1
    for (int r = 0; r < 16; r++) {
        const uint32_t v = __ldg(xw + (size_t)(min(tile, N_TILES - 1) * 16 + r) * 32);
        const float2 q = matvec(lo(v), hi(v), wq, 64, 1);
        aux[r * 32] = matvec(q.x * QSCALE, q.y * QSCALE, wk, 1, 64);
    }
    bar_sync<0, NT>();
#pragma unroll 1
    for (int pass = 0; pass < 2; pass++) {
        const int* dl = pass ? dst : edst;
        const int* sl = pass ? src : esrc;
        const int ne = pass ? N_EDGES : N_XEDGES;
        float den = 0.f;
#pragma unroll 1
        for (int r = 0; r < 16; r++) acc[r * 32] = make_float2(0.f, 0.f);
        int dnext = __ldg(dl + tid);
#pragma unroll 1
        for (int e = tid; e - tid < ne; e += NT) {
            const uint32_t loc = (uint32_t)(dnext - cta * NPC);
            bool pend = e < ne && loc < (uint32_t)NPC;
            if (e + NT < ne) dnext = __ldg(dl + e + NT);
            int more;
            do {
                if (pend) {
                    const uint32_t pos = atomicAdd(cnt + (loc >> 4), 1u);
                    if (pos < (uint32_t)QCAP) { queue[(loc >> 4) * QCAP + pos] = (uint32_t)e * 16u + (loc & 15u); pend = false; }
                }
                more = bar_or(pend);
                if (more || e - tid + NT >= ne) {
                    const int n = min((int)cnt[warp], QCAP);
#pragma unroll 1
                    for (int c = 0; c < n; c++) {
                        const uint32_t q = queue[warp * QCAP + c], r = q & 15u;
                        const int s = __ldg(sl + (q >> 4));
                        const uint32_t v = __ldg(xw + (size_t)s * 32);
                        float w;
                        if (pass) {
                            w = __bfloat162float(dis[s]);
                        } else {
                            const float2 t = aux[r * 32];
                            w = t.x * lo(v) + t.y * hi(v);
#pragma unroll
                            for (int o = 16; o; o >>= 1) w += __shfl_xor_sync(~0u, w, o);
                            w = ex2(w);
                            if (lane == (int)r) den += w;
                        }
                        float2 a = acc[r * 32];
                        a.x += w * lo(v);
                        a.y += w * hi(v);
                        acc[r * 32] = a;
                    }
                    __syncwarp();
                    if (lane == 0) cnt[warp] = 0u;
                    bar_sync<0, NT>();
                }
            } while (more);
        }
#pragma unroll 1
        for (int r = 0; r < 16; r++) {
            const int node = min(tile, N_TILES - 1) * 16 + r;
            const float sc = pass ? __bfloat162float(dis[node]) : 1.f / (__shfl_sync(~0u, den, r) + 1e-9f);
            const float2 a = acc[r * 32];
            const float2 o = matvec(a.x * sc, a.y * sc, pass ? wl : wv, 64, 1);
            if (pass == 0) aux[r * 32] = o;
            else if (tile < N_TILES) reinterpret_cast<uint32_t*>(out)[node * 32 + lane] = pack_bf16(o.x + aux[r * 32].x, o.y + aux[r * 32].y);
        }
    }
}

__device__ __forceinline__ uint32_t bitsel(uint32_t m, uint32_t a, uint32_t b) {
    uint32_t r;
    asm("lop3.b32 %0, %1, %2, %3, 0xE4;" : "=r"(r) : "r"(a), "r"(b), "r"(m));
    return r;
}
template <int N>
__device__ __forceinline__ void post(const uint32_t (&d)[N], const uint32_t (&s)[N], uint32_t tag16, uint32_t tail) {
    uint32_t a[N], b[N];
#pragma unroll
    for (int i = 0; i < N; i++) {
        b[i] = __umulhi(d[i], 11184811u);
        a[i] = atoms_add(sb + SM_HIST + tail * 528 + b[i] * 4, 4u);
    }
    uint32_t v[N];
#pragma unroll
    for (int i = 0; i < N; i++) {
        const uint32_t r = bitsel(63u, s[i], s[i] >> 1) + (s[i] & 64u) * HODD;
        v[i] = bitsel(0xFFC00000u, bitsel(0xF8000000u, r * CMUL, (d[i] - b[i] * NPC) << 18), prmt(r, bitsel(15u, d[i], tag16), 0x5410));
        asm volatile("" : "+r"(v[i]));
    }
    if (!tail && max(a[0], a[N - 1]) >= HEAD) {
#pragma unroll
        for (int i = 0; i < N; i++)
            if (a[i] >= HEAD) a[i] = atoms_add(sb + SM_HIST + 528 + b[i] * 4, 4u);
    }
#pragma unroll
    for (int i = 0; i < N; i++) sts32(a[i] + b[i] * MBS + (sb + SM_MB), v[i]);
}
__device__ __forceinline__ void place4(const uint4& r, uint32_t cur) {
    if (~r.x & 0x06000000u) {
        const uint32_t v[4] = {r.x, r.y, r.z, r.w};
        uint32_t c[4];
#pragma unroll
        for (int i = 0; i < 4; i++) c[i] = atoms_add(cur + ((v[i] >> 20) ^ ((v[i] >> 22) & SWZ)), 4u);
#pragma unroll
        for (int i = 0; i < 4; i++) sts32(sb + abs((int)c[i]), v[i]);
    }
}
__device__ __forceinline__ void settle(uint4& r, const unsigned char* p, uint32_t tagw) {
    int it = 0;
#pragma unroll 1
    while (((r.x ^ tagw) | (r.y ^ tagw) | (r.z ^ tagw) | (r.w ^ tagw)) & TAGM) {
        r = ld_pair(p);
        if (++it > (1 << 22)) { r.x = ~0u; break; }
    }
}
template <int ACQ>
__device__ __forceinline__ void wait_count(const uint32_t* p, uint32_t tagw) {
    const uint32_t go = tagw == TAGM ? 0u : (tagw >> 20) * NCTA;
    uint32_t v;
    int it = 0;
#pragma unroll 1
    do {
        if (ACQ == 1) asm volatile("ld.acquire.gpu.global.u32 %0, [%1];" : "=r"(v) : "l"(p) : "memory");
        else asm volatile("ld.relaxed.gpu.global.u32 %0, [%1];" : "=r"(v) : "l"(p) : "memory");
        if (++it > (1 << 22)) break;
    } while (v != go);
    if (ACQ == 2) asm volatile("ld.acquire.gpu.global.u32 %0, [%1];" : "=r"(v) : "l"(p) : "memory");
}
__device__ __forceinline__ void arrive_count(uint32_t* p) {
    asm volatile("red.relaxed.gpu.global.inc.u32 [%0], %1;" :: "l"(p), "n"(3 * NCTA - 1) : "memory");
}
__device__ __forceinline__ uint32_t now_ns() {
    uint32_t t;
    asm volatile("mov.u32 %0, %%globaltimer_lo;" : "=r"(t) :: "memory");
    return t;
}
__device__ __forceinline__ void wait_until(uint32_t t) {
#pragma unroll 1
    for (int it = 0; it < 4096 && (int)(now_ns() - t) < 0; it++) {}
}
__device__ __forceinline__ void mbar_init(uint32_t mbar, uint32_t n = 1) {
    asm volatile("mbarrier.init.shared.b64 [%0], %1;" :: "r"(mbar), "r"(n) : "memory");
}
template <int PAR = 0>
__device__ __forceinline__ void mbar_wait(uint32_t mbar) {
    uint32_t ok;
    int it = 0;
    do {
        asm volatile("{ .reg .pred p; mbarrier.try_wait.parity.shared.b64 p, [%1], %2; selp.u32 %0, 1, 0, p; }" : "=r"(ok) : "r"(mbar), "n"(PAR) : "memory");
        if (++it > (1 << 22)) break;
    } while (!ok);
}
__device__ __forceinline__ void mbar_arrive(uint32_t mbar) {
    asm volatile("mbarrier.arrive.shared.b64 _, [%0];" :: "r"(mbar) : "memory");
}
__device__ __forceinline__ uint32_t mbar_test(uint32_t mbar) {
    uint32_t ok;
    asm volatile("{ .reg .pred p; mbarrier.test_wait.parity.shared.b64 p, [%1], 0; selp.u32 %0, 1, 0, p; }" : "=r"(ok) : "r"(mbar) : "memory");
    return ok;
}
__device__ __forceinline__ void mbar_expect(uint32_t mbar, uint32_t bytes) {
    asm volatile("mbarrier.arrive.expect_tx.shared.b64 _, [%0], %1;" :: "r"(mbar), "r"(bytes) : "memory");
}
__device__ __forceinline__ void bulk_load(uint32_t dst, const void* src, uint32_t bytes, uint32_t mbar) {
    asm volatile("cp.async.bulk.shared::cluster.global.mbarrier::complete_tx::bytes [%0], [%1], %2, [%3];"
                 :: "r"(dst), "l"(src), "r"(bytes), "r"(mbar) : "memory");
}

__device__ __forceinline__ uint32_t bit_at(int i) {
    uint32_t r;
    asm("shl.b32 %0, 1, %1;" : "=r"(r) : "r"(i));
    return r;
}
__device__ __forceinline__ void plan(int t, int first) {
    const uint32_t tab = sb + SM_RUN + t * TP;
    uint32_t pc = ((t * 4) ^ (SWZ & 64)) + 14 * 128, ps = tab + 32, pd = tab + 92, m0 = 0, m1 = 0, m2 = 0, md = 0;
    int blk = SM_BIN + t * TS + 7 * BP, o = 0, u = 0;
    int nu = lds32(sb + SM_CUR + pc), nd = lds32(sb + SM_CUR + 128 + (pc ^ (SWZ & 32)));
#pragma unroll 1
    for (int k = 15; k > 0; k -= 2, blk -= BP) {
        const int up = nu, dn = nd;
        pc = (pc ^ (SWZ & 64)) - 256;
        nu = lds32(sb + SM_CUR + pc); nd = lds32(sb + SM_CUR + 128 + (pc ^ (SWZ & 32)));
        if (up + dn > 4) o = 1 << 20;
#pragma unroll
        for (int j = 0; j < 2; j++) {
            int n = j ? up - blk - 64 : dn + blk + BP - 68;
            if (k - j < first) n = max(n, 0);
            const bool from = n > 0;
            sts32(from ? ps : pd, from ? (j ? blk + 64 : 4 - dn) - o : (j ? up : blk + BP - 64) - u);
            const int i = from ? o >> 2 : -1;
            m0 |= bit_at(i); m1 |= bit_at(i - 32); m2 |= bit_at(i - 64);
            md |= bit_at(n < 0 ? u >> 2 : -1);
            ps += from ? 4 : 0;
            pd -= n < 0 ? 4 : 0;
            o += n > BP - 128 ? 1 << 20 : max(n, 0);
            u -= min(n, 0);
        }
    }
    u = min(u, 128);
    if (o > 384) {
        o = 0;
        atoms_add(sb + SM_WCNT, 256u);
    }
    const int rest = atoms_add(sb + SM_CUR + 16 * 128 + t * 4, max(o - u, 0));
    sts128v(tab + 16, m1, m2, 0u, 0u);
    sts128v(tab, m0, md, o | u << 16, rest - u);
}
__device__ __forceinline__ void compact(int t, uint32_t lane) {
    const uint32_t tab = sb + SM_RUN + t * TP, le = ~0u >> (31 - lane);
    const uint4 m = lds128(tab);
    const uint32_t o = m.z & 0xFFFFu;
    uint32_t q = lane * 4;
    const uint32_t fr = lds32(tab + 28 + __popc(m.x & le) * 4);
    int to = lds32(tab + 96 - __popc(m.y & le) * 4);
    if (q >= m.z >> 16) to = m.w;
    if (q < o) sts32(sb + abs(to + (int)q), lds32(sb + fr + q));
    if (o > 128) {
        const uint2 g = lds64(tab + 16);
        q += 128;
        if (q < o) sts32(sb - m.w - q, lds32(sb + lds32(tab + 28 + (__popc(m.x) + __popc(g.x & le)) * 4) + q));
        q += 128;
        if (q < o) sts32(sb - m.w - q, lds32(sb + lds32(tab + 28 + (__popc(m.x) + __popc(g.x) + __popc(g.y & le)) * 4) + q));
    }
    wsync();
}
__host__ __device__ constexpr int cut(int i) { return i == 0 ? 0 : i == 1 ? G2 : i == 2 ? 2 * G2 : GOD; }
template <bool FAST>
__global__ void __launch_bounds__(FAST ? NTH : NT, 1)
exphormer_kernel(const __grid_constant__ CUtensorMap head, const __grid_constant__ CUtensorMap inbox, const __nv_bfloat16* __restrict__ x, const int* __restrict__ src, const int* __restrict__ dst,
                 const int* __restrict__ esrc, const int* __restrict__ edst, const __nv_bfloat16* __restrict__ dis,
                 const __nv_bfloat16* __restrict__ wl, const __nv_bfloat16* __restrict__ wq,
                 const __nv_bfloat16* __restrict__ wk, const __nv_bfloat16* __restrict__ wv,
                 __nv_bfloat16* __restrict__ out) {
    extern __shared__ __align__(1024) unsigned char smem[];
    const int tid = threadIdx.x, cta = blockIdx.x;
    const int lane = tid & 31, warp = __shfl_sync(~0u, tid >> 5, 0);
    const bool prod = cta < NPROD;
    constexpr uint32_t MB_EDGE = sb + SM_MISC, MB_BINS = sb + SM_TOTAL - 32;
    const bool go = FAST && (uint32_t)__cvta_generic_to_shared(smem) == sb;
    if (FAST && warp >= NW) {
        asm volatile("setmaxnreg.dec.sync.aligned.u32 24;");
        if (go && warp == NW) {
            const uint32_t t0 = now_ns();
            if (lane == 0) {
#pragma unroll
                for (int i = 0; i < 4; i++) mbar_init(MB_EDGE + i * 8);
#pragma unroll
                for (int i = 5; i < 10; i++) mbar_init(MB_EDGE + i * 8);
                #pragma unroll
                for (int i = 0; i < 4; i++) mbar_init(MB_BINS + i * 8, i == 0 ? NW : i == 1 ? 3 : 1);
                asm volatile("fence.mbarrier_init.release.cluster;" ::: "memory");
                asm volatile("prefetch.tensormap [%0];" :: "l"(&head) : "memory");
                asm volatile("prefetch.tensormap [%0];" :: "l"(&inbox) : "memory");
            }
            wsync();
            bar_arrive<4, NT + 32>();
            if (lane == 0 && prod) {
                const int nex = EX - 2 + (cta & 1) * 4;
                mbar_expect(MB_EDGE + 40, nex * 8);
                bulk_load(sb + SM_EXTRA, dst + NPROD * EC + ((cta * EX) & ~3), nex * 4, MB_EDGE + 40);
                bulk_load(sb + SM_EXTRA + (EX + 2) * 4, src + NPROD * EC + ((cta * EX) & ~3), nex * 4, MB_EDGE + 40);
                wait_until(t0 + TE);
#pragma unroll 1
                for (int i = 0; i < 4; i++) {
                    mbar_expect(MB_EDGE + i * 8, 2 * EC);
                    bulk_load(sb + SM_EDGE + i * 2 * EC, dst + cta * EC + i * (EC / 4), EC, MB_EDGE + i * 8);
                    bulk_load(sb + SM_EDGE + i * 2 * EC + EC, src + cta * EC + i * (EC / 4), EC, MB_EDGE + i * 8);
                }
            }
            wsync();
            if (prod) bar_sync<8, NT + 32>();
            fence_async();
            if (lane == 0 && prod) {
                asm volatile("cp.async.bulk.tensor.3d.global.shared::cta.bulk_group [%0, {%1, %1, %2}], [%3];" :: "l"(&head), "r"(0), "r"(cta), "r"(sb + SM_MB) : "memory");
            }
            wsync();
            bar_sync<5, NT + 96>();
            const uint32_t t1 = now_ns();
            fence_async();
            const uint32_t tagw = lds32(sb + SM_TAG + 4);
            wait_until(t1 + XD);
            if (lane == 0) {
                if (prod)
                    asm volatile("cp.async.bulk.tensor.3d.global.shared::cta.bulk_group [%0, {%1, %1, %2}], [%3];" :: "l"(&inbox), "r"(0), "r"(cta), "r"(sb + SM_MB + HEAD) : "memory");
                asm volatile("cp.async.bulk.commit_group; cp.async.bulk.wait_group 0;" ::: "memory");
                arrive_count(g_count);
                asm volatile("{ .reg .b64 t; mov.u64 t, %%globaltimer; red.relaxed.gpu.global.max.u64 [%0], t; }" :: "l"(g_count + 36) : "memory");
#pragma unroll
                for (int i = 0; i < 3; i++) mbar_expect(MB_EDGE + 48 + i * 8, cut(i + 1) - cut(i));
            }
            wsync();
            bar_sync<2, 96>();
            if (lane == 0) {
                const unsigned char* g = g_rec + cta * GBKT;
                asm volatile("" : "+l"(g));
                wait_until(t0 + TH0);
#pragma unroll
                for (int i = 0; i < 3; i++) {
                    if (i == 1) wait_count<false>(g_count, tagw);
                    bulk_load(sb + SM_MB + cut(i), g + cut(i), cut(i + 1) - cut(i), MB_EDGE + 48 + i * 8);
                }
            }
            wsync();
            if (lane == 0) {
                mbar_wait(MB_EDGE + 56);
                wait_count<true>(g_count + 32, tagw);
                const uint32_t t = ld_pair(g_count + 36).x + TD;
                wait_until(t);
                sts32(sb + SM_TAG + 8, now_clk());
            }
            wsync();
            bar_sync<6, NTH>();
            if (lane < NW) plan(lane, 5 + 3 * CI);
            wsync();
            if (lane == 0) mbar_arrive(MB_BINS + 16);
            mbar_wait(MB_BINS + 8);
            const int t = min(lane, NW - 1);
            uint32_t f = __any_sync(~0u, lds32(sb + SM_WCNT) || lds32(sb + SM_CUR + 16 * 128 + t * 4) + SM_LAST - 4 + t * TL > TCAP);
            if (lane < 2) st_pair(g_flag + cta * 2 + lane, make_uint4(tagw | f, 0u, 0u, 0u));
            int it = 0;
#pragma unroll 1
            do {
                f = 0;
#pragma unroll
                for (int i = 0; i < 5; i++) {
                    uint32_t v;
                    asm volatile("ld.relaxed.gpu.global.u32 %0, [%1];" : "=r"(v) : "l"(g_flag + min(lane + i * 32, NCTA - 1) * 2) : "memory");
                    f |= v ^ tagw;
                }
            } while (f > 1u && ++it < (1 << 20));
            f = __any_sync(~0u, f);
            if (lane == 0) { sts32(sb + SM_WCNT, f); mbar_arrive(MB_BINS + 24); }
        } else if (go && warp == NW + 1) {
            const int n = min(NPC, N_NODES - cta * NPC) * 128;
            bar_sync<3, NT + 32>();
            fence_async();
#pragma unroll 1
            for (int p = 0; p < 2; p++) {
                if (lane == 0) {
                    if (p) asm volatile("cp.async.bulk.prefetch.L2.global [%0], %1;" :: "l"(edst + cta * NPC * 4), "r"(n / 8) : "memory");
                    if (p) mbar_wait(MB_EDGE + 64);
#pragma unroll 1
                    for (int o = p * 8192; o < n; o += 16384)
                        asm volatile("cp.async.bulk.global.shared::cta.bulk_group [%0], [%1], %2;"
                                     :: "l"(g_h + (cta * STG + o) / 2 + p * (HODD * 8192 - 4096)), "r"(sb + SM_STAGE + o), "r"(min(n - o, 8192)) : "memory");
                }
                wsync();
                if (lane == 0) {
                    asm volatile("cp.async.bulk.commit_group; cp.async.bulk.wait_group 0;" ::: "memory");
                }
                wsync();
                if (p) bar_arrive<6, NTH>();
                if (lane == 0) {
                    asm volatile("fence.acq_rel.gpu;" ::: "memory");
                    arrive_count(g_count + 32 + p * 32);
                }
            }
            if (lane == 0) {
                wait_count<2>(g_count + 64, lds32(sb + SM_TAG + 4));
                asm volatile("mbarrier.arrive.shared.b64 _, [%0];" :: "r"(MB_EDGE + 72) : "memory");
            }
        } else if (go && warp > NW + 1) {
            wait_until(now_ns() + TW);
#pragma unroll 4
            for (int r = warp & 1; r < 64; r += 2)
                cp4(sb + SM_W + 2 * 8192 + r * 128 + (((((lane >> 2) & 4) | (lane & 3)) ^ (r & 7)) << 4) + (lane & 12), wv + r * 64 + lane * 2);
            cp_commit();
            cp_wait<0>();
            fence_async();
            bar_sync<5, NT + 96>();
            uint32_t last[3];
#pragma unroll
            for (int j = 0; j < 3; j++) {
                const uint32_t c = (tid & 63) + j * 64;
                last[j] = prod && c < NCTA ? lds32(sb + SM_MB + c * MBS + PIECE - 4) : ~0u;
            }
#pragma unroll 1
            for (uint32_t c = tid & 63; c < NCTA; c += 64) {
#pragma unroll 1
                for (uint32_t o = 0; ~last[0] & 0x06000000u; o += 32) {
                    if (o == NMORE * 16) {
                        if (lds32(sb + SM_HIST + 528 + c * 4) > MBS) atoms_add(sb + SM_WCNT, 256u);
                        break;
                    }
                    const uint4 u = lds128(sb + SM_MB + c * MBS + PIECE + o), v = lds128(sb + SM_MB + c * MBS + PIECE + o + 16);
                    unsigned char* g = g_rec + c * GBKT + GOD + cta * NMORE * 16 + o;
                    st_pair(g, u);
                    st_pair(g + 16, v);
                    last[0] = v.w;
                }
                last[0] = last[1]; last[1] = last[2];
            }
            wsync();
            bar_arrive<2, 96>();
            const uint32_t tagw = lds32(sb + SM_TAG + 4);
            unsigned char* gin = g_rec + cta * GBKT;
            mbar_wait(MB_EDGE + 48);
            mbar_wait(MB_EDGE + 56);
            mbar_wait(MB_EDGE + 64);
#pragma unroll
            for (int j = 0; j < 2; j++) {
                const int q = NPROD * HEAD + ((tid & 63) + j * 64 + 1) * (PIECE - HEAD) - 16;
                uint4 r;
                r.x = r.y = r.z = r.w = lds32(sb + SM_MB + q + 12);
                settle(r, gin + q, tagw);
                last[j] = r.w;
            }
            wsync();
            bar_arrive<6, NTH>();
            mbar_wait(MB_BINS);
            gin += GOD + (tid & 63) * NMORE * 16;
#pragma unroll 1
            for (int j = 0; j < 2; j++) {
#pragma unroll 1
                for (uint32_t o = 0; o < NMORE * 16 && (~last[0] & 0x06000000u); o += 32) {
                    uint4 u[2] = {ld_pair(gin + o), ld_pair(gin + o + 16)};
#pragma unroll
                    for (int i = 0; i < 2; i++) {
                        settle(u[i], gin + o + i * 16, tagw);
                        st_pair(gin + o + i * 16, make_uint4(0u, 0u, 0u, 0u));
                        constexpr uint32_t M = 0xF8000000u, L = (NCLS - 1u) << 27;
                        place4(make_uint4(bitsel(M, L, u[i].x), bitsel(M, L, u[i].y), bitsel(M, L, u[i].z), bitsel(M, L, u[i].w)), sb + SM_CUR - (tagw >> 20));
                    }
                    last[0] = u[1].w;
                }
                last[0] = last[1];
                gin += 64 * NMORE * 16;
            }
            wsync();
            if (lane == 0) {
                mbar_arrive(MB_BINS + 8);
            }
        }
        if (go && warp == NW + 1) {
            wsync();
            uint32_t odd = 0;
#pragma unroll 3
            for (int i = 0; i < NPC; i += 32) {
                const uint32_t node = min(cta * NPC + i + lane, N_NODES - 1);
                const uint4 v = __ldg(reinterpret_cast<const uint4*>(edst) + node);
                odd |= (v.x ^ node) | (v.y ^ node) | (v.z ^ node) | (v.w ^ node);
            }
            if (odd) atoms_add(sb + SM_WCNT, 256u);
            wsync();
            if (lane == 0) { mbar_arrive(MB_BINS + 8); }
        }
        return;
    }
    if (!go) {
        slow_cta(x, src, dst, esrc, edst, dis, wl, wq, wk, wv, out, smem);
        return;
    }

    const int nex = prod ? EX - 2 + (cta & 1) * 4 : 0;
    const int tile = cta * NW + warp;
    const uint32_t st0 = sb + SM_STAGE + warp * 2048;
    if (tid == 704) {
        mbar_init(MB_EDGE + 32);
        asm volatile("fence.mbarrier_init.release.cluster;" ::: "memory");
        const int nown = min(NPC, N_NODES - cta * NPC);
        mbar_expect(MB_EDGE + 32, nown * 18 + 16);
        bulk_load(sb + SM_TAG, g_count, 16, MB_EDGE + 32);
        bulk_load(sb + SM_ES, esrc + cta * NPC * 4, nown * 16, MB_EDGE + 32);
        bulk_load(sb + SM_DIS, dis + cta * NPC, nown * 2, MB_EDGE + 32);
    }
    {
        const int i = tid & 127;
        const uint32_t d = (i >> 3) * 128 + (((i ^ (i >> 3)) & 7) << 4);
        if (warp < 16) {
            cp16(sb + SM_W + 8192 + (warp >> 2) * 2048 + d, wl + tid * 8);
        } else if (warp < 20) {
#pragma unroll
            for (int q = 0; q < 4; q++) {
                cp16(sb + SM_QK + d + q * 2048, wq + i * 8 + q * 1024);
                cp16(sb + SM_QK + d + q * 2048 + 8192, wk + i * 8 + q * 1024);
            }
        }
    }
    cp_commit();
    bar_sync<0, NT>();
    {
        const uint32_t d = st0 + (lane >> 3) * 128 + (((lane & 7) ^ (lane >> 3)) << 4);
        const char* s = reinterpret_cast<const char*>(x) + min(tile, N_TILES - 1) * 2048 + lane * 16;
#pragma unroll
        for (int i = 0; i < 4; i++) cp16((d ^ ((i & 1) * 64)) + i * 512, s + i * 512);
        cp_commit();
    }
    {
        int v = SM_BIN + lane * TS + (warp >> 1) * BP;
        if (warp & 1) v = 4 - BP - v;
        if (warp == 16) v = 4 - SM_LAST - lane * TL;
        if (lane >= NW) v = SM_DUMP + (tid & 0x7C);
        if (warp == NCLS) v = 0;
        if (warp < NCLS || tid == NCLS * 32 + (31 ^ (SWZ & 32) / 4)) sts32(sb + SM_CUR + ((tid * 4) ^ (tid & SWZ)), v);
        const int k = tid - (NT - 264);
        if (k >= 0) sts32(sb + SM_HIST + k * 4, k < 132 ? 0 : HEAD);
    }
    asm volatile("setmaxnreg.inc.sync.aligned.u32 80;");
    cp_wait<1>();
    fence_async();
    if ((warp >> 2) == 4) {
        asm volatile("bar.sync 1, 128;" ::: "memory");
        const uint32_t pa = ((warp & 3) * 16 + (lane & 15)) * 128 + (((lane >> 4) ^ (lane & 7)) << 4);
        uint32_t a[16];
        float t[8][4];
#pragma unroll
        for (int s = 0; s < 4; s++) ldsm4(a[4 * s], a[4 * s + 1], a[4 * s + 2], a[4 * s + 3], (pa ^ (s << 5)) + sb + SM_QK);
        undef_acc(t);
        wg_gemm<true>(t, a, sb + SM_QK + 8192, 0u);
        to_afrag(a, t, QSCALE, QSCALE);
#pragma unroll
        for (int s = 0; s < 4; s++) stsm4((pa ^ (s << 5)) + sb + SM_W, a[4 * s], a[4 * s + 1], a[4 * s + 2], a[4 * s + 3]);
        fence_async();
    }
    mbar_wait(MB_EDGE + 32);
    const uint32_t dx = st0 + (lane >> 3) * 256 + (((lane & 7) ^ ((lane >> 3) * 2)) << 4);
    const uint32_t ea = sb + SM_ES + (min(tile, N_TILES - 1) - cta * NW) * 256 + (lane >> 3) * 32;
    const char* xx = reinterpret_cast<const char*>(x) + (lane & 7) * 16;
#define NB(J, OFS) issue_rows(dx + (OFS), xx, lds32(ea + (J) * 4), lds32(ea + 16 + (J) * 4), lds32(ea + 128 + (J) * 4), lds32(ea + 144 + (J) * 4));
    const uint32_t tagw = (lds32(sb + SM_TAG) / NCTA + 1u) << 20;
    {
        const uint32_t nul = ((cta & 15) << 27) | ((24 + (cta >> 4)) << 22) | tagw;
#pragma unroll
        for (int i = 0; i < 4; i++) sts128(st0 + 2 * STG + lane * 16 + i * 512, nul);
        if (tid == 160) sts32(sb + SM_TAG + 4, tagw);
    }
    bar_sync<4, NT + 32>();
    NB(0, STG)
    uint32_t tq[16], y[16];
    float acc[8][4];
    float e0 = 0.f, e1 = 0.f;
    const uint32_t lb = st0 + ((lane & 7) + (lane >> 4) * 8) * 128 + ((((lane >> 3) & 1) ^ (lane & 7)) << 4);
    {
        cp_wait<1>(); wsync();
#pragma unroll
        for (int s = 0; s < 4; s++) ldsm4(y[4 * s], y[4 * s + 2], y[4 * s + 1], y[4 * s + 3], lb ^ (s << 5));
        undef_acc(acc);
        wg_gemm(acc, y, sb + SM_W + 8192, 0u);
        const uint32_t pd = sb + SM_DIS + warp * 32 + (lane >> 2) * 2;
        to_afrag(tq, acc, __uint_as_float(lds16(pd) << 16), __uint_as_float(lds16(pd + 16) << 16));
        const uint32_t ha = st0 + (lane >> 2) * 128 + (lane & 7) * 16;
        const bool odd = lane & 4;
#pragma unroll
        for (int i = 0; i < 2; i++) {
            sts128v(ha + i * 1024, odd ? tq[8 + i] : tq[i], odd ? tq[10 + i] : tq[2 + i], odd ? tq[12 + i] : tq[4 + i], odd ? tq[14 + i] : tq[6 + i]);
            sts128v((ha ^ 64) + i * 1024, odd ? tq[i] : tq[8 + i], odd ? tq[2 + i] : tq[10 + i], odd ? tq[4 + i] : tq[12 + i], odd ? tq[6 + i] : tq[14 + i]);
        }
        undef_acc(acc);
        wg_gemm(acc, y, sb + SM_W, 0u);
        to_afrag(tq, acc);
    }
#define POST() {                                                                                     \
            const uint32_t ea = sb + SM_EDGE + j * 2 * EC + tid * 8;                                 \
            const uint2 dv = lds64(ea), sv = lds64(ea + EC);                                         \
            post<2>({dv.x, dv.y}, {sv.x, sv.y}, tagw >> 16, j >> 1);                                 \
            if (j == 1) bar_arrive<8, NT + 32>();                                 \
        }
    bar_arrive<3, NT + 32>();
    if (tid < nex) {
        mbar_wait(MB_EDGE + 40);
        post<1>({lds32(sb + SM_EXTRA + tid * 4)}, {lds32(sb + SM_EXTRA + (EX + 2) * 4 + tid * 4)}, tagw >> 16, 0);
    }
    uint32_t nb[6];
#pragma unroll
    for (int i = 0; i < 6; i++) nb[i] = lds32(ea + 4 + (i >> 1) * 4 + (i & 1) * 128) | lds32(ea + 20 + (i >> 1) * 4 + (i & 1) * 128) << 16;
#define NBR(J, OFS) { issue_rows(dx + (OFS), xx, nb[2 * (J) - 2] & 0xFFFFu, nb[2 * (J) - 2] >> 16, nb[2 * (J) - 1] & 0xFFFFu, nb[2 * (J) - 1] >> 16); }
#define ATTN(N, OFS, K) { tq[0] = pin(tq[0], lds32(sb + SM_TAG)); cp_wait<N>(); wsync(); uint32_t l_ = lb + (OFS); if (K == 2) asm("" : "+r"(l_) : "n"(K)); attn_chunk(y, e0, e1, tq, l_, lane); wsync(); }
    int j = prod ? 0 : 4;
#pragma unroll 1
    for (; j < JMAX && __all_sync(~0u, mbar_test(MB_EDGE + j * 8)); j++) {
        POST()
    }
#pragma unroll
    for (int i = 0; i < 16; i++) y[i] = 0u;
    ATTN(0, STG, 0)
    NBR(1, STG)
#pragma unroll 1
    for (; j < 4; j++) {
        mbar_wait(MB_EDGE + j * 8);
        POST()
    }
    bar_sync<5, NT + 96>();
    const unsigned char* gin = g_rec + cta * GBKT + tid * 16;
    const uint32_t l0 = sb + SM_BIN + warp * TS;
    const uint32_t own = ((l0 + 127) & ~127u) - st0;
    NBR(2, own)
#define BINS() {                                                                                \
        const uint32_t a = l0 + (lane >> 3) * BP + (lane & 4) * (BP / 4 - 32) + (lane & 7) * 16;          \
        sts128(a, NUL);                                                                         \
        sts128(a + 4 * BP, NUL);                                                                  \
        sts128(sb + SM_LAST - 512 + warp * TL + lane * 16, NUL);                                \
    }

#define GEMM3() {                                                                                    \
            const uint32_t rden = __shfl_sync(~0u, pack_bf16(__fdividef(1.f, e0 + 1e-9f), __fdividef(1.f, e1 + 1e-9f)), (lane & 28) | (lane >> 3)); \
            const uint32_t q0 = prmt(rden, rden, 0x1010), q1 = prmt(rden, rden, 0x3232);             \
            _Pragma("unroll") for (int i = 0; i < 16; i++) y[i] = fma_bf2(y[i], (i & 1) ? q1 : q0, 0x80008000u); \
            undef_acc(acc);                                                                          \
            wg_gemm<false, false>(acc, y, sb + SM_W + 2 * 8192, 0u);                                            \
        }
    {
        ATTN(1, STG, 1)
        ATTN(0, own, 2)
        NBR(3, STG)
        BINS()
        wsync();
        if (lane == 0) mbar_arrive(MB_BINS);
        const uint32_t cur = sb + SM_CUR - (tagw >> 20);
#define PLACE(O, N) if ((N) == G2 || (NT - 1 - tid) * 16 < (N)) {                           \
            uint4 r = lds128(sb + SM_MB + (O) - (G2 - (N)) + tid * 16);                     \
            settle(r, gin + (O) - (G2 - (N)), tagw);                                        \
            place4(r, cur);                                                                 \
        }
        ATTN(0, STG, 3)
        GEMM3()
        mbar_wait(MB_BINS);
        mbar_wait(MB_EDGE + 48);
        PLACE(0, G2)
        wg_wait(acc, y);
        mbar_wait(MB_EDGE + 56);
        PLACE(cut(1), G2)
        mbar_wait(MB_EDGE + 64);
        PLACE(cut(2), GOD - cut(2))
    }
    bar_sync<6, NTH>();

    {
        const int lg = lane >> 3, lc = lane & 7;
        const uint32_t da = pin(st0 + lg * 256 + ((lc ^ (lg * 2)) << 4), tagw), db = pin(da ^ 0x90u, tagw);
        const uint32_t ka = pin(lg * 16, tagw), kt = pin((lane & 3) * 8, tagw);
        const char* xl = reinterpret_cast<const char*>(g_h) + lc * 16 + 0xFFFF * 128;
        uint32_t p0 = l0, p1 = l0 + BP - 64, so, c0, c1, c2;
        {
            const uint4 q0 = lds128(p0 + ka), q1 = lds128(p1 + ka), q2 = lds128(p0 + BP + ka);
            issue_list<true>(da, db, q0, xl);
            issue_list<true>(da + STG, db + STG, q1, xl);
            issue_list<true>(da + 2 * STG, db + 2 * STG, q2, xl);
            c0 = rows_of(q0, kt); c1 = rows_of(q1, kt); c2 = rows_of(q2, kt);
        }
        {
            uint32_t la[4];
#pragma unroll
            for (int q = 0; q < 4; q++) la[q] = pin((st0 + (lane & 15) * 128 + (((lane >> 4) ^ (lane & 7)) << 4)) ^ (q * 32), tagw);
            const uint32_t code = pin((uint32_t)((lane >> 2) + (tagw >> 16)) * 0x10001u + 0x04080400u, tagw);
            const uint32_t pd = sb + SM_DIS + warp * 32 + (lane >> 2) * 2;
            const uint32_t w0 = lds16(pd) * 0x10001u, w1 = lds16(pd + 16) * 0x10001u;
#define STEP(OFS, P, Q)                                                         \
            {                                                                   \
                const uint4 q = lds128((Q) + ka);                               \
                chunk(acc, la, OFS, P, kt, code, w0, w1, da, db, q, xl); \
            }
            uint32_t due = __shfl_sync(~0u, lds32(sb + SM_TAG + 8), 0) + PB + warp * ST;
#pragma unroll 1
            for (int i = 0;; i++) {
                STEP(0, c0, p1 + BP)
                wait_clk(due - PP / 3);
                if (i == 4) break;
                STEP(STG, c1, p0 + 2 * BP)
                wait_clk(due);
                due += PP;
                if (i == 1) mbar_wait(MB_EDGE + 72);
                if (i == CI) { mbar_wait(MB_BINS + 16); compact(warp, (code & 7) * 4 + (kt >> 3)); due += CA; }
                STEP(2 * STG, c2, p1 + 2 * BP)
                wait_clk(due - 2 * PP / 3);
                const uint32_t pn = p0 + 2 * BP;
                p0 = p1 + BP; p1 = pn;
            }
#undef STEP
            int lane;
            asm volatile("mov.u32 %0, %%laneid;" : "=r"(lane));
            p0 = sb + SM_LAST - 64 + warp * TL;
            mbar_wait(MB_BINS + 8);
            p1 = p0 - __shfl_sync(~0u, (p0 + 60 + 63 - sb + lds32(sb + SM_CUR + 16 * 128 + warp * 4)) & 0x1C0u, 0);
            so = 0;
#pragma unroll 1
            do {
                so = so == 2 * STG ? 0 : so + STG;
                uint4 q;
                if (p0 > p1) q = lds128(p0 + ka);
                chunk(acc, la, so, c1, kt, code, w0, w1, da, db, q, xl, p0 > p1);
                const uint32_t c = c1;
                c1 = c2; c2 = c0; c0 = c;
                p0 -= 64;
            } while (p0 != p1 - 192);
            to_afrag(y, acc);
            store_tile(out, tile, lane, y);
        }
    }
    mbar_wait(MB_BINS + 24);
    if (__builtin_expect(lds32(sb + SM_WCNT), 0)) slow_cta(x, src, dst, esrc, edst, dis, wl, wq, wk, wv, out, smem);
}


}

extern "C" void kernel_launch(void* const* d_in, const int* in_sizes, int n_in, void* d_out, int out_size) {
    (void)in_sizes; (void)n_in; (void)out_size;
    const __nv_bfloat16* x   = (const __nv_bfloat16*)d_in[0];
    const int* src           = (const int*)d_in[1];
    const int* dst           = (const int*)d_in[2];
    const int* esrc          = (const int*)d_in[3];
    const int* edst          = (const int*)d_in[4];
    const __nv_bfloat16* dis = (const __nv_bfloat16*)d_in[5];
    const __nv_bfloat16* wl  = (const __nv_bfloat16*)d_in[6];
    const __nv_bfloat16* wq  = (const __nv_bfloat16*)d_in[7];
    const __nv_bfloat16* wk  = (const __nv_bfloat16*)d_in[8];
    const __nv_bfloat16* wv  = (const __nv_bfloat16*)d_in[9];
    __nv_bfloat16* out = (__nv_bfloat16*)d_out;

    static int fast = -1;
    static CUtensorMap map[2];
    if (fast < 0) {
        cudaFuncSetAttribute(exphormer_kernel<true>, cudaFuncAttributeMaxDynamicSharedMemorySize, SM_TOTAL);
        cudaFuncSetAttribute(exphormer_kernel<false>, cudaFuncAttributeMaxDynamicSharedMemorySize, SM_TOTAL);
        int dev = 0, sms = 0, occ = 0;
        cudaGetDevice(&dev);
        cudaDeviceGetAttribute(&sms, cudaDevAttrMultiProcessorCount, dev);
        cudaOccupancyMaxActiveBlocksPerMultiprocessor(&occ, exphormer_kernel<true>, NTH, SM_TOTAL);
        fast = (sms * occ >= NCTA) ? 1 : 0;
        void *fn = nullptr, *rec = nullptr;
        cudaDriverEntryPointQueryResult found;
        cudaGetSymbolAddress(&rec, g_rec);
        cudaGetDriverEntryPoint("cuTensorMapEncodeTiled", &fn, cudaEnableDefault, &found);
        for (int i = 0; i < 2; i++) {
            const cuuint64_t dim[3] = {(i ? PIECE - HEAD : HEAD) / 4u, NCTA, NPROD}, pitch[2] = {GBKT, dim[0] * 4};
            const cuuint32_t box[3] = {MBS / 4, NCTA, 1}, one[3] = {1, 1, 1};
            if (!fn || reinterpret_cast<decltype(&cuTensorMapEncodeTiled)>(fn)(map + i, CU_TENSOR_MAP_DATA_TYPE_UINT32, 3, (char*)rec + i * HEAD * NPROD, dim, pitch, box, one,
                    CU_TENSOR_MAP_INTERLEAVE_NONE, CU_TENSOR_MAP_SWIZZLE_NONE, CU_TENSOR_MAP_L2_PROMOTION_NONE, CU_TENSOR_MAP_FLOAT_OOB_FILL_NONE) != CUDA_SUCCESS)
                fast = 0;
        }
    }
    if (fast) exphormer_kernel<true><<<NCTA, NTH, SM_TOTAL>>>(map[0], map[1], x, src, dst, esrc, edst, dis, wl, wq, wk, wv, out);
    else      exphormer_kernel<false><<<NCTA, NT, SM_TOTAL>>>(map[0], map[1], x, src, dst, esrc, edst, dis, wl, wq, wk, wv, out);
}
```
